```python
import torch

def _softmax(x, axis=-1):
    return torch.softmax(x, dim=axis)
def _gelu(x):
    return torch.nn.functional.gelu(x, approximate="tanh")
def _silu(x):
    return torch.nn.functional.silu(x)
def _sigmoid(x):
    return torch.sigmoid(x)
def _layernorm(x, axis=-1, eps=1e-5):
    m = x.mean(dim=axis, keepdim=True)
    v = x.var(dim=axis, keepdim=True, unbiased=False)
    return (x - m) / torch.sqrt(v + eps)
def _scatter_add(tgt, idx, src, axis=0):
    return tgt.clone().index_add_(axis, idx, src)
def _segment_sum(src, seg, n):
    out = torch.zeros((n,) + src.shape[1:], dtype=src.dtype)
    return out.index_add_(0, seg, src)
def _pad(x, pw):
    flat = tuple(v for pair in reversed(pw) for v in pair)
    return torch.nn.functional.pad(x, flat)

kernel_name = 'parallel_sum__ssm_conv_s4__mixer_channel_mlp__prompt'

def setup_inputs():

    _w = (lambda a: (lambda t: t.to(torch.bfloat16) if t.is_floating_point() else t)(torch.as_tensor(a)))
    def _A_setup():
        B, L, D, N = 1, 2048, 512, 128
        A_re = -(lambda _x: torch.exp(torch.as_tensor(_x)))((lambda *s: torch.randn(*s, dtype=torch.bfloat16) * 3.2)(D, N))
        A_im = torch.pi * (lambda *s: torch.randn(*s, dtype=torch.bfloat16) * 0.05)(D, N)
        B_re = (lambda *s: torch.randn(*s, dtype=torch.bfloat16) * 0.1)(D, N)
        B_im = (lambda *s: torch.randn(*s, dtype=torch.bfloat16) * 0.1)(D, N)
        C_re = (lambda *s: torch.randn(*s, dtype=torch.bfloat16) * 0.1)(D, N)
        C_im = (lambda *s: torch.randn(*s, dtype=torch.bfloat16) * 0.1)(D, N)
        log_dt = (lambda *s: torch.randn(*s, dtype=torch.bfloat16) * 0.05)(D) * 0.5 - 4.0
        Dskip = (lambda *s: torch.randn(*s, dtype=torch.bfloat16) * 0.05)(D)
        return {
            "u": _w((lambda *s: torch.randn(*s, dtype=torch.bfloat16) * 0.05)(B, L, D)),
            "A_re": _w(A_re),
            "A_im": _w(A_im),
            "B_re": _w(B_re),
            "B_im": _w(B_im),
            "C_re": _w(C_re),
            "C_im": _w(C_im),
            "log_dt": _w(log_dt),
            "Dskip": _w(Dskip),
        }
    _A_in = _A_setup()

    def _B_setup():
        B, S, D, F = 1, 2048, 512, 1792
        return {
            "x": _w((lambda *s: torch.randn(*s, dtype=torch.bfloat16) * 0.05)(B, S, D)),
            "w1": _w((lambda *s: torch.randn(*s, dtype=torch.bfloat16) * 1.6)(D, F) * (D ** -0.5)),
            "b1": _w((lambda *s: torch.randn(*s, dtype=torch.bfloat16) * 0.8)(F)),
            "w2": _w((lambda *s: torch.randn(*s, dtype=torch.bfloat16) * 0.05)(F, D) * (F ** -0.5)),
            "b2": _w((lambda *s: torch.randn(*s, dtype=torch.bfloat16) * 0.05)(D)),
        }
    _B_in = _B_setup()

    return {
        "A_u": _A_in["u"],
        "A_A_re": _A_in["A_re"],
        "A_A_im": _A_in["A_im"],
        "A_B_re": _A_in["B_re"],
        "A_B_im": _A_in["B_im"],
        "A_C_re": _A_in["C_re"],
        "A_C_im": _A_in["C_im"],
        "A_log_dt": _A_in["log_dt"],
        "A_Dskip": _A_in["Dskip"],
        "B_x": _B_in["x"],
        "B_w1": _B_in["w1"],
        "B_b1": _B_in["b1"],
        "B_w2": _B_in["w2"],
        "B_b2": _B_in["b2"],
    }

def reference(A_u, A_A_re, A_A_im, A_B_re, A_B_im, A_C_re, A_C_im, A_log_dt, A_Dskip, B_x, B_w1, B_b1, B_w2, B_b2):
    def _A_ref(u, A_re, A_im, B_re, B_im, C_re, C_im, log_dt, Dskip):
        Bsz, L, D = u.shape
        dt = torch.exp(log_dt)[:, None]
        A = A_re + 1j * A_im
        Bc = B_re + 1j * B_im
        Cc = C_re + 1j * C_im
        logdA = dt * A
        dB = dt * Bc
        l = (lambda x, dt: x.to(dt))(torch.arange(L), A_re.dtype)
        P = torch.exp(logdA[:, :, None] * l[None, None, :])
        K = torch.einsum("dn,dnl,dn->dl", Cc, P, dB).real
        L2 = 2 * L
        Kp = _pad(K, ((0, 0), (0, L)))
        up = (lambda x, *d: x.permute(*d))(u, 0, 2, 1)
        up = _pad(up, ((0, 0), (0, 0), (0, L)))
        Kf = (lambda x, axes=(-2,-1): torch.fft.rfft2(x.float(), dim=axes))(Kp[:, None, :], axes=(-2, -1))
        Uf = (lambda x, axes=(-2,-1): torch.fft.rfft2(x.float(), dim=axes))(up[:, :, None, :], axes=(-2, -1))
        Yf = Uf * Kf[None, :, :, :]
        y = (lambda x, s, axes=(-2,-1): torch.fft.irfft2(x, s=s, dim=axes).to(torch.bfloat16))(Yf, (1, L2), axes=(-2, -1))[:, :, 0, :L]
        y = (lambda x, *d: x.permute(*d))(y, 0, 2, 1) + u * Dskip[None, None, :]
        return y

    def _B_ref(x, w1, b1, w2, b2):
        y = _layernorm(x, axis=-1)
        h = _gelu(torch.einsum("bsd,df->bsf", y, w1) + b1)
        return torch.einsum("bsf,fd->bsd", h, w2) + b2

    x = A_u
    xn = _layernorm(x, axis=-1)
    return x + _A_ref(xn, A_A_re, A_A_im, A_B_re, A_B_im, A_C_re, A_C_im, A_log_dt, A_Dskip) + _B_ref(xn, B_w1, B_b1, B_w2, B_b2)
```

```cpp
#include <cuda_runtime.h>
#include <cuda_bf16.h>
#include <cuda.h>
#include <stdint.h>

namespace {

constexpr int L_ = 2048, D_ = 512, F_ = 1792, NM_ = 128;
constexpr int NCTA = 128;

constexpr uint32_t S1_BYTES = 24576, S1_N = 6;
constexpr uint32_t RING_BYTES = S1_BYTES * S1_N;
constexpr uint32_t S2_BYTES = 32768, S2_N = 4;
constexpr uint32_t XT_OFF = RING_BYTES;
constexpr uint32_t XT_CH = 4352;
constexpr uint32_t SSM_OFF = XT_OFF + 4 * XT_CH;
constexpr uint32_t KG_BUF = 28672;
constexpr uint32_t LN_OFF = XT_OFF;
constexpr uint32_t KC_OFF = SSM_OFF;
constexpr uint32_t KC_COPY = 4160, KC_CH = 2 * KC_COPY;
constexpr uint32_t KD_OFF = SSM_OFF + 2 * KG_BUF;
constexpr uint32_t KD_CH = 1312;
constexpr uint32_t RED_OFF = SSM_OFF;
constexpr uint32_t CM_OFF = SSM_OFF + 4 * KC_CH;
constexpr uint32_t MISC_OFF = KD_OFF + 4 * KD_CH;
constexpr uint32_t TAB1_OFF = MISC_OFF;
constexpr uint32_t STAT_OFF = MISC_OFF + 1792;
constexpr uint32_t B2_OFF = MISC_OFF + 2816;
constexpr uint32_t WS_OFF = KD_OFF;
constexpr uint32_t BAR_OFF = MISC_OFF + 3072;
constexpr uint32_t EPOCH_OFF = BAR_OFF + 320;
constexpr uint32_t SMEM_USED = EPOCH_OFF + 16 + 256;
constexpr uint32_t SMEM_BYTES = SMEM_USED;
static_assert(CM_OFF + 11 * 2048 <= KD_OFF && (BAR_OFF & 7) == 0, "smem");
static_assert(XT_OFF + 4 * XT_CH <= SSM_OFF && (SSM_OFF & 1023) == 0, "smem");
static_assert(SMEM_BYTES <= 232448, "smem");

enum { B_FULL1 = 0, B_EMPTY1 = 6, B_FULL2 = 14, B_EMPTY2 = 18, B_TAB = 22, B_HST = 23  , B_HFREE = 25,
       B_LN = 26, B_CS = 27, B_KRDY = 28  , B_XT = 32, B_CONV = 33, B_PFREE = 34, B_RED = 35, B_COUNT = 36 };

__device__ __forceinline__ uint32_t s2_off(int s) { return RING_BYTES - S2_BYTES * (s + 1); }

__device__ __align__(1024) __nv_bfloat16 g_h[L_ * F_];
__device__ __align__(1024) __nv_bfloat16 g_xnT[D_ * L_];
__device__ __align__(1024) __nv_bfloat16 g_zT[D_ * L_];
__device__ __align__(256) float2 g_stats[L_];
__device__ __align__(256) float g_w1sum[4 * F_];
__device__ __align__(256) unsigned g_cnt[64 * 32];
enum { C_START = 0, C_LN = 32, C_Z = 64, C_H = 96   };
#define TS(i)
#define TS_DUMP()
#define DBG(b) 0
#define TS_G(v)

__device__ __forceinline__ uint32_t smem_u32(const void* p) { return (uint32_t)__cvta_generic_to_shared(p); }
__device__ __forceinline__ void mbar_init(uint32_t bar, uint32_t cnt) {
  asm volatile("mbarrier.init.shared::cta.b64 [%0], %1;" ::"r"(bar), "r"(cnt) : "memory");
}
__device__ __forceinline__ void mbar_arrive(uint32_t bar) {
  asm volatile("mbarrier.arrive.shared::cta.b64 _, [%0];" ::"r"(bar) : "memory");
}
__device__ __forceinline__ void mbar_arrive_remote_light(uint32_t bar_cluster) {
  asm volatile("mbarrier.arrive.shared::cluster.b64 _, [%0];" ::"r"(bar_cluster) : "memory");
}
__device__ __forceinline__ void mbar_expect(uint32_t bar, uint32_t bytes) {
  asm volatile("mbarrier.arrive.expect_tx.shared::cta.b64 _, [%0], %1;" ::"r"(bar), "r"(bytes) : "memory");
}
__device__ __forceinline__ void mbar_wait(uint32_t bar, uint32_t parity) {
#pragma unroll 1
  for (int it = 0; it < (1 << 22); it++) {
    uint32_t ok;
    asm volatile("{\n.reg .pred p;\nmbarrier.try_wait.parity.shared::cta.b64 p, [%1], %2;\nselp.u32 %0, 1, 0, p;\n}"
                 : "=r"(ok) : "r"(bar), "r"(parity) : "memory");
    if (ok) return;
  }
  __trap();
}
__device__ __forceinline__ void mbar_wait_cluster(uint32_t bar, uint32_t parity) {
#pragma unroll 1
  for (int it = 0; it < (1 << 22); it++) {
    uint32_t ok;
    asm volatile("{\n.reg .pred p;\nmbarrier.try_wait.parity.acquire.cluster.shared::cta.b64 p, [%1], %2;\nselp.u32 %0, 1, 0, p;\n}"
                 : "=r"(ok) : "r"(bar), "r"(parity) : "memory");
    if (ok) return;
  }
  __trap();
}
__device__ __forceinline__ bool elect() {
  uint32_t p;
  asm volatile("{\n.reg .pred p;\nelect.sync _|p, 0xffffffff;\nselp.u32 %0, 1, 0, p;\n}" : "=r"(p));
  return p != 0;
}
__device__ __forceinline__ void bar_sync(int id, int n) { asm volatile("bar.sync %0, %1;" ::"r"(id), "r"(n) : "memory"); }
__device__ __forceinline__ void fence_async_smem() { asm volatile("fence.proxy.async.shared::cta;" ::: "memory"); }
__device__ __forceinline__ void fence_async_global() { asm volatile("fence.proxy.async.global;" ::: "memory"); }
__device__ __forceinline__ void tma_ld2(uint32_t dst, const CUtensorMap* m, int c0, int c1, uint32_t bar) {
  asm volatile("cp.async.bulk.tensor.2d.shared::cluster.global.mbarrier::complete_tx::bytes [%0], [%1, {%3, %4}], [%2];"
               ::"r"(dst), "l"(m), "r"(bar), "r"(c0), "r"(c1) : "memory");
}
__device__ __forceinline__ void tma_ld3(uint32_t dst, const CUtensorMap* m, int c0, int c1, int c2, uint32_t bar) {
  asm volatile("cp.async.bulk.tensor.3d.shared::cluster.global.mbarrier::complete_tx::bytes [%0], [%1, {%3, %4, %5}], [%2];"
               ::"r"(dst), "l"(m), "r"(bar), "r"(c0), "r"(c1), "r"(c2) : "memory");
}
__device__ __forceinline__ void tma_ld3_mc(uint32_t dst, const CUtensorMap* m, int c0, int c1, int c2, uint32_t bar) {
  asm volatile("cp.async.bulk.tensor.3d.shared::cluster.global.mbarrier::complete_tx::bytes.multicast::cluster [%0], [%1, {%3, %4, %5}], [%2], %6;"
               ::"r"(dst), "l"(m), "r"(bar), "r"(c0), "r"(c1), "r"(c2), "h"((uint16_t)3) : "memory");
}
__device__ __forceinline__ void tma_st2(const CUtensorMap* m, int c0, int c1, uint32_t src) {
  asm volatile("cp.async.bulk.tensor.2d.global.shared::cta.bulk_group [%0, {%2, %3}], [%1];"
               ::"l"(m), "r"(src), "r"(c0), "r"(c1) : "memory");
}
__device__ __forceinline__ void tma_st3(const CUtensorMap* m, int c0, int c1, int c2, uint32_t src) {
  asm volatile("cp.async.bulk.tensor.3d.global.shared::cta.bulk_group [%0, {%2, %3, %4}], [%1];"
               ::"l"(m), "r"(src), "r"(c0), "r"(c1), "r"(c2) : "memory");
}
__device__ __forceinline__ void bulk_ld(uint32_t dst, const void* src, uint32_t bytes, uint32_t bar) {
  asm volatile("cp.async.bulk.shared::cluster.global.mbarrier::complete_tx::bytes [%0], [%1], %2, [%3];"
               ::"r"(dst), "l"(src), "r"(bytes), "r"(bar) : "memory");
}
__device__ __forceinline__ void bulk_commit() { asm volatile("cp.async.bulk.commit_group;" ::: "memory"); }
__device__ __forceinline__ void bulk_wait_read0() { asm volatile("cp.async.bulk.wait_group.read 0;" ::: "memory"); }
__device__ __forceinline__ void bulk_wait0() { asm volatile("cp.async.bulk.wait_group 0;" ::: "memory"); }
__device__ __forceinline__ void prefetch_map(const CUtensorMap* m) { asm volatile("prefetch.tensormap [%0];" ::"l"(m) : "memory"); }
__device__ __forceinline__ void l2_prefetch(const void* p, uint32_t bytes) {
  asm volatile("cp.async.bulk.prefetch.L2.global [%0], %1;" ::"l"(p), "r"(bytes) : "memory");
}
__device__ __forceinline__ void signal_gpu(unsigned* p) {
  asm volatile("red.release.gpu.global.add.u32 [%0], 1;" ::"l"(p) : "memory");
}
__device__ __forceinline__ void wait_gpu(const unsigned* p, unsigned target) {
#pragma unroll 1
  for (int it = 0; it < (1 << 22); it++) {
    unsigned v;
    asm volatile("ld.acquire.gpu.global.u32 %0, [%1];" : "=r"(v) : "l"(p) : "memory");
    if ((int)(v - target) >= 0) return;
    __nanosleep(32);
  }
  __trap();
}
__device__ __forceinline__ uint64_t mk_desc(uint32_t addr, uint32_t lbo, uint32_t sbo, uint32_t swz) {
  return (uint64_t)((addr & 0x3FFFF) >> 4) | ((uint64_t)(lbo >> 4) << 16) | ((uint64_t)(sbo >> 4) << 32) | ((uint64_t)swz << 62);
}
#define WG_FENCE() asm volatile("wgmma.fence.sync.aligned;" ::: "memory")
#define WG_COMMIT() asm volatile("wgmma.commit_group.sync.aligned;" ::: "memory")
#define WG_WAIT(n) asm volatile("wgmma.wait_group.sync.aligned %0;" ::"n"(n) : "memory")
template <int N> __device__ __forceinline__ void pin(float (&d)[N]) {
#pragma unroll
  for (int i = 0; i < N; i++) asm volatile("" : "+f"(d[i])::"memory");
}
__device__ __forceinline__ void wgmma_n96_tb(float (&d)[48], uint64_t da, uint64_t db, int scale_d) {
  asm volatile("{\n.reg .pred p;\nsetp.ne.b32 p, %50, 0;\n"
    "wgmma.mma_async.sync.aligned.m64n96k16.f32.bf16.bf16 {%0, %1, %2, %3, %4, %5, %6, %7, %8, %9, %10, %11, %12, %13, %14, %15, %16, %17, %18, %19, %20, %21, %22, %23, %24, %25, %26, %27, %28, %29, %30, %31, %32, %33, %34, %35, %36, %37, %38, %39, %40, %41, %42, %43, %44, %45, %46, %47}, %48, %49, p, 1, 1, 0, 1;\n}"
   : "+f"(d[0]), "+f"(d[1]), "+f"(d[2]), "+f"(d[3]), "+f"(d[4]), "+f"(d[5]), "+f"(d[6]), "+f"(d[7]), "+f"(d[8]), "+f"(d[9]), "+f"(d[10]), "+f"(d[11]), "+f"(d[12]), "+f"(d[13]), "+f"(d[14]), "+f"(d[15]), "+f"(d[16]), "+f"(d[17]), "+f"(d[18]), "+f"(d[19]), "+f"(d[20]), "+f"(d[21]), "+f"(d[22]), "+f"(d[23]), "+f"(d[24]), "+f"(d[25]), "+f"(d[26]), "+f"(d[27]), "+f"(d[28]), "+f"(d[29]), "+f"(d[30]), "+f"(d[31]), "+f"(d[32]), "+f"(d[33]), "+f"(d[34]), "+f"(d[35]), "+f"(d[36]), "+f"(d[37]), "+f"(d[38]), "+f"(d[39]), "+f"(d[40]), "+f"(d[41]), "+f"(d[42]), "+f"(d[43]), "+f"(d[44]), "+f"(d[45]), "+f"(d[46]), "+f"(d[47])
   : "l"(da), "l"(db), "r"(scale_d));
}
__device__ __forceinline__ void wgmma_n128_tb(float (&d)[64], uint64_t da, uint64_t db, int scale_d) {
  asm volatile("{\n.reg .pred p;\nsetp.ne.b32 p, %66, 0;\n"
    "wgmma.mma_async.sync.aligned.m64n128k16.f32.bf16.bf16 {%0, %1, %2, %3, %4, %5, %6, %7, %8, %9, %10, %11, %12, %13, %14, %15, %16, %17, %18, %19, %20, %21, %22, %23, %24, %25, %26, %27, %28, %29, %30, %31, %32, %33, %34, %35, %36, %37, %38, %39, %40, %41, %42, %43, %44, %45, %46, %47, %48, %49, %50, %51, %52, %53, %54, %55, %56, %57, %58, %59, %60, %61, %62, %63}, %64, %65, p, 1, 1, 0, 1;\n}"
   : "+f"(d[0]), "+f"(d[1]), "+f"(d[2]), "+f"(d[3]), "+f"(d[4]), "+f"(d[5]), "+f"(d[6]), "+f"(d[7]), "+f"(d[8]), "+f"(d[9]), "+f"(d[10]), "+f"(d[11]), "+f"(d[12]), "+f"(d[13]), "+f"(d[14]), "+f"(d[15]), "+f"(d[16]), "+f"(d[17]), "+f"(d[18]), "+f"(d[19]), "+f"(d[20]), "+f"(d[21]), "+f"(d[22]), "+f"(d[23]), "+f"(d[24]), "+f"(d[25]), "+f"(d[26]), "+f"(d[27]), "+f"(d[28]), "+f"(d[29]), "+f"(d[30]), "+f"(d[31]), "+f"(d[32]), "+f"(d[33]), "+f"(d[34]), "+f"(d[35]), "+f"(d[36]), "+f"(d[37]), "+f"(d[38]), "+f"(d[39]), "+f"(d[40]), "+f"(d[41]), "+f"(d[42]), "+f"(d[43]), "+f"(d[44]), "+f"(d[45]), "+f"(d[46]), "+f"(d[47]), "+f"(d[48]), "+f"(d[49]), "+f"(d[50]), "+f"(d[51]), "+f"(d[52]), "+f"(d[53]), "+f"(d[54]), "+f"(d[55]), "+f"(d[56]), "+f"(d[57]), "+f"(d[58]), "+f"(d[59]), "+f"(d[60]), "+f"(d[61]), "+f"(d[62]), "+f"(d[63])
   : "l"(da), "l"(db), "r"(scale_d));
}
__device__ __forceinline__ void wgmma_n160(float (&d)[80], uint64_t da, uint64_t db, int scale_d) {
  asm volatile("{\n.reg .pred p;\nsetp.ne.b32 p, %82, 0;\n"
    "wgmma.mma_async.sync.aligned.m64n160k16.f32.bf16.bf16 {%0, %1, %2, %3, %4, %5, %6, %7, %8, %9, %10, %11, %12, %13, %14, %15, %16, %17, %18, %19, %20, %21, %22, %23, %24, %25, %26, %27, %28, %29, %30, %31, %32, %33, %34, %35, %36, %37, %38, %39, %40, %41, %42, %43, %44, %45, %46, %47, %48, %49, %50, %51, %52, %53, %54, %55, %56, %57, %58, %59, %60, %61, %62, %63, %64, %65, %66, %67, %68, %69, %70, %71, %72, %73, %74, %75, %76, %77, %78, %79}, %80, %81, p, 1, 1, 0, 0;\n}"
   : "+f"(d[0]), "+f"(d[1]), "+f"(d[2]), "+f"(d[3]), "+f"(d[4]), "+f"(d[5]), "+f"(d[6]), "+f"(d[7]), "+f"(d[8]), "+f"(d[9]), "+f"(d[10]), "+f"(d[11]), "+f"(d[12]), "+f"(d[13]), "+f"(d[14]), "+f"(d[15]), "+f"(d[16]), "+f"(d[17]), "+f"(d[18]), "+f"(d[19]), "+f"(d[20]), "+f"(d[21]), "+f"(d[22]), "+f"(d[23]), "+f"(d[24]), "+f"(d[25]), "+f"(d[26]), "+f"(d[27]), "+f"(d[28]), "+f"(d[29]), "+f"(d[30]), "+f"(d[31]), "+f"(d[32]), "+f"(d[33]), "+f"(d[34]), "+f"(d[35]), "+f"(d[36]), "+f"(d[37]), "+f"(d[38]), "+f"(d[39]), "+f"(d[40]), "+f"(d[41]), "+f"(d[42]), "+f"(d[43]), "+f"(d[44]), "+f"(d[45]), "+f"(d[46]), "+f"(d[47]), "+f"(d[48]), "+f"(d[49]), "+f"(d[50]), "+f"(d[51]), "+f"(d[52]), "+f"(d[53]), "+f"(d[54]), "+f"(d[55]), "+f"(d[56]), "+f"(d[57]), "+f"(d[58]), "+f"(d[59]), "+f"(d[60]), "+f"(d[61]), "+f"(d[62]), "+f"(d[63]), "+f"(d[64]), "+f"(d[65]), "+f"(d[66]), "+f"(d[67]), "+f"(d[68]), "+f"(d[69]), "+f"(d[70]), "+f"(d[71]), "+f"(d[72]), "+f"(d[73]), "+f"(d[74]), "+f"(d[75]), "+f"(d[76]), "+f"(d[77]), "+f"(d[78]), "+f"(d[79])
   : "l"(da), "l"(db), "r"(scale_d));
}

__device__ __forceinline__ void mma16816(float* d, uint32_t a0, uint32_t a1, uint32_t a2, uint32_t a3, uint32_t b0, uint32_t b1) {
  asm("mma.sync.aligned.m16n8k16.row.col.f32.bf16.bf16.f32 {%0,%1,%2,%3}, {%4,%5,%6,%7}, {%8,%9}, {%0,%1,%2,%3};"
               : "+f"(d[0]), "+f"(d[1]), "+f"(d[2]), "+f"(d[3]) : "r"(a0), "r"(a1), "r"(a2), "r"(a3), "r"(b0), "r"(b1));
}
__device__ __forceinline__ void ldsm4(uint32_t& r0, uint32_t& r1, uint32_t& r2, uint32_t& r3, uint32_t addr) {
  asm volatile("ldmatrix.sync.aligned.m8n8.x4.shared.b16 {%0,%1,%2,%3}, [%4];" : "=r"(r0), "=r"(r1), "=r"(r2), "=r"(r3) : "r"(addr) : "memory");
}
__device__ __forceinline__ void ldsm4t(uint32_t& r0, uint32_t& r1, uint32_t& r2, uint32_t& r3, uint32_t addr) {
  asm volatile("ldmatrix.sync.aligned.m8n8.x4.trans.shared.b16 {%0,%1,%2,%3}, [%4];" : "=r"(r0), "=r"(r1), "=r"(r2), "=r"(r3) : "r"(addr) : "memory");
}
__device__ __forceinline__ void stsm4(uint32_t addr, uint32_t r0, uint32_t r1, uint32_t r2, uint32_t r3) {
  asm volatile("stmatrix.sync.aligned.m8n8.x4.shared.b16 [%0], {%1,%2,%3,%4};" ::"r"(addr), "r"(r0), "r"(r1), "r"(r2), "r"(r3) : "memory");
}
__device__ __forceinline__ uint32_t movmat(uint32_t a) {
  uint32_t d;
  asm volatile("movmatrix.sync.aligned.m8n8.trans.b16 %0, %1;" : "=r"(d) : "r"(a));
  return d;
}
__device__ __forceinline__ uint32_t lds32(uint32_t a) { uint32_t v; asm volatile("ld.shared.u32 %0, [%1];" : "=r"(v) : "r"(a) : "memory"); return v; }
__device__ __forceinline__ uint32_t lds16(uint32_t a) { uint16_t v; asm volatile("ld.shared.u16 %0, [%1];" : "=h"(v) : "r"(a) : "memory"); return v; }
__device__ __forceinline__ float4 lds128f(uint32_t a) {
  float4 v; asm volatile("ld.shared.v4.f32 {%0,%1,%2,%3}, [%4];" : "=f"(v.x), "=f"(v.y), "=f"(v.z), "=f"(v.w) : "r"(a) : "memory"); return v;
}
__device__ __forceinline__ float2 lds64f(uint32_t a) {
  float2 v; asm volatile("ld.shared.v2.f32 {%0,%1}, [%2];" : "=f"(v.x), "=f"(v.y) : "r"(a) : "memory"); return v;
}
template <typename T> __device__ __forceinline__ T lds(uint32_t a) {
  return *reinterpret_cast<const T*>(__cvta_shared_to_generic(a));
}
__device__ __forceinline__ void sts32(uint32_t a, uint32_t v) { asm volatile("st.shared.u32 [%0], %1;" ::"r"(a), "r"(v) : "memory"); }
__device__ __forceinline__ void sts16(uint32_t a, uint32_t v) { asm volatile("st.shared.u16 [%0], %1;" ::"r"(a), "h"((uint16_t)v) : "memory"); }
__device__ __forceinline__ void sts128(uint32_t a, uint32_t x, uint32_t y, uint32_t z, uint32_t w) {
  asm volatile("st.shared.v4.u32 [%0], {%1,%2,%3,%4};" ::"r"(a), "r"(x), "r"(y), "r"(z), "r"(w) : "memory");
}
__device__ __forceinline__ void sts64f(uint32_t a, float x, float y) { asm volatile("st.shared.v2.f32 [%0], {%1,%2};" ::"r"(a), "f"(x), "f"(y) : "memory"); }
__device__ __forceinline__ uint32_t pack2(float lo, float hi) {
  uint32_t r; asm("cvt.rn.bf16x2.f32 %0, %1, %2;" : "=r"(r) : "f"(hi), "f"(lo)); return r;
}
__device__ __forceinline__ float bf_lo(uint32_t v) { return __uint_as_float(v << 16); }
__device__ __forceinline__ float bf_hi(uint32_t v) { return __uint_as_float(v & 0xffff0000u); }
__device__ __forceinline__ float bf_round(float v) { return bf_lo(pack2(v, 0.f)); }
__device__ __forceinline__ uint4 ldg128(const void* p) { return __ldg(reinterpret_cast<const uint4*>(p)); }
__device__ __forceinline__ float warp_sum(float v) {
#pragma unroll
  for (int o = 16; o > 0; o >>= 1) v += __shfl_xor_sync(0xffffffffu, v, o);
  return v;
}
struct cf { float r, i; };
__device__ __forceinline__ cf cmul(cf a, cf b) { return {fmaf(a.r, b.r, -a.i * b.i), fmaf(a.r, b.i, a.i * b.r)}; }
__device__ __forceinline__ cf csqr(cf a) { return {fmaf(a.r, a.r, -a.i * a.i), (a.r + a.r) * a.i}; }
__device__ __forceinline__ cf cexp_at(float lr2, float lit, float x) {
  float m; asm("ex2.approx.ftz.f32 %0, %1;" : "=f"(m) : "f"(lr2 * x));
  float t = lit * x; t -= rintf(t); t *= 6.283185307179586f;
  return {m * __cosf(t), m * __sinf(t)};
}
__device__ __forceinline__ float gelu_tanh(float hv) {
  float u = hv * fmaf(hv * hv, 8.f * 0.7978845608028654f * 0.044715f, 2.f * 0.7978845608028654f);
  float th; asm("tanh.approx.f32 %0, %1;" : "=f"(th) : "f"(u));
  return fmaf(hv, th, hv);
}

template <int JLO, int JHI>
__device__ __forceinline__ void conv_mma(float (&acc)[JHI - JLO + 1][4], uint32_t sb, int ch_local, int lane, int rho0, int rho1) {
  constexpr int NX = (JHI + 2) / 2 * 2;
  const int g = lane >> 2, c = lane & 3;
#pragma unroll
  for (int j = 0; j <= JHI - JLO; j++) { acc[j][0] = acc[j][1] = acc[j][2] = acc[j][3] = 0.f; }
  const uint32_t kbase = sb + KC_OFF + ch_local * KC_CH + (g & 1) * KC_COPY + 4 * (1024 - ((g + 1) >> 1) + c);
  const uint32_t xbase = sb + XT_OFF + ch_local * XT_CH + 256 + (lane >> 4) * 256;
  const int khalf = (lane >> 3) & 1, n = lane & 7;
#pragma unroll 1
  for (int rho = rho0; rho < rho1; rho++) {
    uint32_t X[NX][2];
    const int rr = n - rho;
    const uint32_t xa = xbase + rr * 32 + ((khalf ^ ((rr >> 2) & 1)) << 4);
#pragma unroll
    for (int i = NX / 2 - 1; i >= 0; i--) ldsm4(X[2 * i][0], X[2 * i][1], X[2 * i + 1][0], X[2 * i + 1][1], xa + i * 512);
    const uint32_t ka = kbase - 32 * rho;
#pragma unroll
    for (int kap = 0; kap <= JHI; kap++) {
      const uint32_t a0 = lds<uint32_t>(ka - 256 * kap), a1 = lds<uint32_t>(ka - 256 * kap - 16), a2 = lds<uint32_t>(ka - 256 * kap + 16);
      uint32_t a3;
      asm volatile("prmt.b32 %0, %1, %1, 0x3210;" : "=r"(a3) : "r"(a0));
#pragma unroll
      for (int j = (kap > JLO ? kap : JLO); j <= JHI; j++) mma16816(acc[j - JLO], a0, a1, a2, a3, X[j - kap][0], X[j - kap][1]);
    }
  }
}
__device__ __forceinline__ void conv_store(const float (&a)[4], int ch_global, int j, int lane) {
  uint32_t* zp = reinterpret_cast<uint32_t*>(g_zT + (size_t)ch_global * L_ + 128 * j + 16 * (lane >> 2) + 2 * (lane & 3));
  const uint32_t q0 = movmat(pack2(a[0], a[1])), q1 = movmat(pack2(a[2], a[3]));
  zp[0] = q0;
  zp[4] = q1;
}

__device__ __forceinline__ float kgen_batch(uint32_t buf, int w, int lane, float dt, const float (&pv)[6]) {
  const float lr2 = (dt * pv[0]) * 1.4426950408889634f, lit = (dt * pv[1]) * 0.15915494309189535f;
  const cf CB = cmul({pv[4], pv[5]}, {dt * pv[2], dt * pv[3]});
  const uint32_t bufA = buf + w * 2048 + (lane & 3) * 4, bufB = buf + 8192 + w * 5120 + (lane & 3) * 4;
  const int ck = lane >> 2;
  auto stB = [&](int i, cf v) { sts32(bufB + i * 128 + ((ck ^ (i & 7)) << 4), pack2(v.r, v.i)); };
  auto stA = [&](int j, cf v) { sts32(bufA + j * 128 + ((ck ^ (j & 7)) << 4), pack2(v.r, -v.i)); };
  const cf z1 = cexp_at(lr2, lit, 1.f), z8 = cexp_at(lr2, lit, 8.f), U = cexp_at(lr2, lit, 128.f);
  const cf z2 = csqr(z1), z3 = cmul(z2, z1), z4 = csqr(z2), z5 = cmul(z4, z1), z6 = csqr(z3), z7 = cmul(z4, z3);
  stB(0, {1.f, 0.f}); stB(1, z1); stB(2, z2); stB(3, z3); stB(4, z4); stB(5, z5); stB(6, z6); stB(7, z7);
  stB(8, U); stB(9, cmul(U, z1)); stB(10, cmul(U, z2)); stB(11, cmul(U, z3)); stB(12, cmul(U, z4));
  stB(13, cmul(U, z5)); stB(14, cmul(U, z6)); stB(15, cmul(U, z7));
  const cf U2 = csqr(U), U3 = cmul(U2, U), U4 = csqr(U2), U5 = cmul(U4, U), U6 = csqr(U3), U7 = cmul(U4, U3), U8 = csqr(U4);
  stB(16, U2); stB(17, cmul(U2, z2)); stB(18, cmul(U2, z4)); stB(19, cmul(U2, z6));
  stB(20, U3); stB(21, cmul(U3, z2)); stB(22, cmul(U3, z4)); stB(23, cmul(U3, z6));
  stB(24, U4); stB(25, cmul(U4, z4)); stB(26, U5); stB(27, cmul(U5, z4));
  stB(28, U6); stB(29, cmul(U6, z4)); stB(30, U7); stB(31, cmul(U7, z4));
  stB(32, U8); stB(33, cmul(U8, U)); stB(34, cmul(U8, U2)); stB(35, cmul(U8, U3));
  stB(36, cmul(U8, U4)); stB(37, cmul(U8, U5)); stB(38, cmul(U8, U6)); stB(39, cmul(U8, U7));
  const cf U16 = csqr(U8), z16 = csqr(z8);
  cf ve = CB, vo = cmul(CB, z8);
#pragma unroll
  for (int j = 0; j < 16; j += 2) {
    stA(j, ve); stA(j + 1, vo);
    if (j < 14) { ve = cmul(ve, z16); vo = cmul(vo, z16); }
  }
  return CB.r * U16.r - CB.i * U16.i;
}

struct Params {
  const __nv_bfloat16 *x, *a_re, *a_im, *b_re, *b_im, *c_re, *c_im, *log_dt, *dskip, *w1, *b1, *w2, *b2;
};

__global__ void __cluster_dims__(2, 1, 1) __launch_bounds__(512, 1)
fused_kernel(const __grid_constant__ CUtensorMap tmW1g, const __grid_constant__ CUtensorMap tmW1s, const __grid_constant__ CUtensorMap tmW1h,
             const __grid_constant__ CUtensorMap tmHst, const __grid_constant__ CUtensorMap tmHld,
             const __grid_constant__ CUtensorMap tmW2, const __grid_constant__ CUtensorMap tmXe,
             const __grid_constant__ CUtensorMap tmX1, const __grid_constant__ CUtensorMap tmZ, const __grid_constant__ CUtensorMap tmOut, const Params P) {
  extern __shared__ __align__(1024) uint8_t smem_raw[];
  const uint32_t sb = smem_u32(smem_raw);
  if (sb & 1023u) __trap();
  const uint32_t bars = sb + BAR_OFF;
  auto BAR = [&](int i) { return bars + 8u * i; };
  const int tid = threadIdx.x, warp = tid >> 5, lane = tid & 31, wg = tid >> 7;
  const int cl = blockIdx.x >> 1, rank = blockIdx.x & 1;
  int grp, pp;
  if (cl < 4) { grp = 0; pp = 4 + cl; }
  else if (cl < 36) { grp = (cl - 4) & 7; pp = (cl - 4) >> 3; }
  else { grp = 1 + (cl - 36) % 7; pp = 4 + (cl - 36) / 7; }
  const int rb1 = 2 * grp + rank, js = pp;
  const int rb = 2 * grp + (pp >> 2), cb = pp & 3;
  const int cid = rb1 * 8 + js;

  const int w1g = 7 * (js >> 1) + 4 * (js & 1), w1h = 14 * (js >> 1) + 6 + (js & 1);
  TS_G(_g0);
  TS(0);
  if (wg == 3 && elect()) {
    if (warp == 12) {
      for (int i = 0; i < (int)S1_N; i++) mbar_init(BAR(B_FULL1 + i), 1);
      fence_async_smem();
      mbar_expect(BAR(B_FULL1), S1_BYTES);
      tma_ld2(sb, &tmX1, 0, rb1 * 128, BAR(B_FULL1));
      tma_ld3(sb + 8192, &tmW1g, 0, 0, w1g, BAR(B_FULL1));
      tma_ld3(sb + 16384, &tmW1s, 0, 0, w1g + 2, BAR(B_FULL1));
      tma_ld3(sb + 20480, &tmW1h, 0, 0, w1h, BAR(B_FULL1));
      TS(1);
    } else {
      prefetch_map(warp == 13 ? &tmW1g : warp == 14 ? &tmW1s : &tmW1h);
    }
  }
  auto cta_sync_and_cluster_arrive = [&]() {
    asm volatile("bar.sync 0;" ::: "memory");
    asm volatile("barrier.cluster.arrive.relaxed.aligned;" ::: "memory");
  };

  if (wg == 3) {
    asm volatile("setmaxnreg.dec.sync.aligned.u32 40;");
    if (elect()) {
      if (warp == 13) {
        for (int i = 0; i < (int)S1_N; i++) mbar_init(BAR(B_EMPTY1 + i), 16);
        for (int i = 0; i < (int)S2_N; i++) { mbar_init(BAR(B_FULL2 + i), 1); mbar_init(BAR(B_EMPTY2 + i), 8); }
      } else if (warp == 14) {
        mbar_init(BAR(B_TAB), 1); mbar_init(BAR(B_HST), 4); mbar_init(BAR(B_HST + 1), 4); mbar_init(BAR(B_HFREE), 1);
        mbar_init(BAR(B_LN), 9); mbar_init(BAR(B_CS), 8);
        if (!DBG(4)) l2_prefetch(P.w1 + (size_t)cid * 7168, 14336);
      } else if (warp == 15) {
        for (int i = 0; i < 4; i++) mbar_init(BAR(B_KRDY + i), 1);
        mbar_init(BAR(B_XT), 1); mbar_init(BAR(B_CONV), 12); mbar_init(BAR(B_PFREE), 1); mbar_init(BAR(B_RED), 1);
        mbar_expect(BAR(B_RED), 32768);
      }
      asm volatile("fence.mbarrier_init.release.cluster;" ::: "memory");
    }
    __syncwarp();
    cta_sync_and_cluster_arrive();
    if (warp == 12) {
      asm volatile("barrier.cluster.wait.acquire.aligned;" ::: "memory");
      if (DBG(1)) mbar_wait(BAR(B_CS), 0);
      for (int kt = 1; kt < 16; kt++) {
        const int st = kt % S1_N;
        if (DBG(2) && kt == 2) mbar_wait(BAR(B_CS), 0);
        if (kt >= (int)S1_N) mbar_wait(BAR(B_EMPTY1 + st), ((kt / S1_N) - 1) & 1);
        if (elect()) {
          mbar_expect(BAR(B_FULL1 + st), S1_BYTES);
          tma_ld2(sb + st * S1_BYTES, &tmX1, kt * 32, rb1 * 128, BAR(B_FULL1 + st));
          if (rank == 0) {
            tma_ld3_mc(sb + st * S1_BYTES + 8192, &tmW1g, 0, kt * 32, w1g, BAR(B_FULL1 + st));
          } else {
            tma_ld3_mc(sb + st * S1_BYTES + 16384, &tmW1s, 0, kt * 32, w1g + 2, BAR(B_FULL1 + st));
            tma_ld3_mc(sb + st * S1_BYTES + 20480, &tmW1h, 0, kt * 32, w1h, BAR(B_FULL1 + st));
          }
        }
        __syncwarp();
      }
      mbar_wait(BAR(B_EMPTY1 + 3), 0);
      mbar_wait(BAR(B_TAB), 0);
      const unsigned ep1 = lds32(sb + EPOCH_OFF) + 1;
      if (lane == 0) { wait_gpu(&g_cnt[C_H + 32 * (rb * 2 + rank)], ep1 * 8); fence_async_global(); }
      __syncwarp();
      TS(8);
      for (int it = 0; it < 15; it++) {
        const int s = it % S2_N;
        if (it >= (int)S2_N) mbar_wait(BAR(B_EMPTY2 + s), ((it / S2_N) - 1) & 1);
        if (it == 2) mbar_wait(BAR(B_HFREE), 0);
        if (it == 14) { if (lane == 0) { wait_gpu(&g_cnt[C_Z], ep1 * NCTA); fence_async_global(); } __syncwarp(); }
        if (elect()) {
          const uint32_t dst = sb + s2_off(s);
          mbar_expect(BAR(B_FULL2 + s), S2_BYTES);
          if (it < 14) {
            tma_ld2(dst, &tmHld, rank * 896 + it * 64, rb * 128, BAR(B_FULL2 + s));
            tma_ld3(dst + 16384, &tmW2, 0, rank * 896 + it * 64, cb * 2, BAR(B_FULL2 + s));
          } else {
            tma_ld2(dst, &tmXe, cb * 128 + rank * 64, rb * 128, BAR(B_FULL2 + s));
            tma_ld3(dst + 16384, &tmZ, 0, cb * 128 + rank * 64, rb * 2, BAR(B_FULL2 + s));
          }
        }
        __syncwarp();
      }
    } else if (warp == 13) {
      asm volatile("barrier.cluster.wait.acquire.aligned;" ::: "memory");
      for (int w = 0; w < 2; w++) {
        mbar_wait(BAR(B_HST + w), 0);
        if (lane == 0) { tma_st3(&tmHst, 0, rb1 * 128 + w * 64, js * 7, sb + w * 28672); bulk_commit(); }
        __syncwarp();
      }
      if (lane == 0) {
        bulk_wait_read0(); mbar_arrive(BAR(B_HFREE));
        bulk_wait0(); fence_async_global();
        unsigned* p = &g_cnt[C_H + 32 * (rb1 * 2 + (js >> 2))];
        asm volatile("red.release.gpu.global.add.u32 [%0], 2;" ::"l"(p) : "memory");
      }
      __syncwarp();
      TS(7);
    } else if (warp == 14) {
      mbar_wait(BAR(B_CS), 0);
      if (cid < 112) {
        float2 s = make_float2(0.f, 0.f);
#pragma unroll
        for (int k = 0; k < 8; k++) { const float2 v = lds<float2>(sb + WS_OFF + k * 256 + lane * 8); s.x += v.x; s.y += v.y; }
        *reinterpret_cast<float2*>(&g_w1sum[(cid & 3) * F_ + (cid >> 2) * 64 + lane * 2]) = s;
      }
      sts64f(sb + B2_OFF + lane * 8, __bfloat162float(P.b2[cb * 128 + rank * 64 + 2 * lane]), __bfloat162float(P.b2[cb * 128 + rank * 64 + 2 * lane + 1]));
      __syncwarp();
      if (lane == 0) { mbar_arrive(BAR(B_LN)); l2_prefetch(P.w2 + (size_t)cid * 7168, 14336); }
      TS(17);
      asm volatile("barrier.cluster.wait.acquire.aligned;" ::: "memory");
      mbar_wait(BAR(B_CONV), 0);
      if (lane == 0) {
        uint32_t remote;
        asm volatile("mapa.shared::cluster.u32 %0, %1, %2;" : "=r"(remote) : "r"(BAR(B_PFREE)), "r"(rank ^ 1));
        mbar_arrive_remote_light(remote);
        signal_gpu(&g_cnt[C_Z]);
      }
      __syncwarp();
      TS(10);
    } else {
      unsigned ep = 0;
      if (lane == 0) ep = atomicAdd(&g_cnt[C_START], 1u) / NCTA;
      float b1v[7];
#pragma unroll
      for (int i = 0; i < 7; i++) b1v[i] = 0.5f * __bfloat162float(P.b1[js * 224 + (lane + 32 * (i + (js & 1))) % 224]);
      asm volatile("barrier.cluster.wait.acquire.aligned;" ::: "memory");
      mbar_wait(BAR(B_LN), 0);
      if (lane == 0) {
        signal_gpu(&g_cnt[C_LN]);
        sts32(sb + EPOCH_OFF, ep);
        wait_gpu(&g_cnt[C_LN], (ep + 1) * NCTA);
      }
      __syncwarp();
      TS(3);
      if (lane < 16) {
#pragma unroll
        for (int w = 0; w < 4; w++) sts128(sb + XT_OFF + w * XT_CH + lane * 16, 0, 0, 0, 0);
      }
      __syncwarp();
      if (lane == 0) {
        fence_async_global(); fence_async_smem();
        mbar_expect(BAR(B_XT), 4 * 4096);
        for (int w = 0; w < 4; w++) bulk_ld(sb + XT_OFF + w * XT_CH + 256, g_xnT + (size_t)(cid * 4 + w) * L_, 4096, BAR(B_XT));
      }
#pragma unroll
      for (int i = 0; i < 4; i++) {
        const float2 v = __ldcg(&g_stats[rb1 * 128 + lane + 32 * i]);
        sts64f(sb + STAT_OFF + (lane + 32 * i) * 8, 0.5f * v.x, 0.5f * v.y);
      }
#pragma unroll
      for (int i = 0; i < 7; i++) {
        const float* p = &g_w1sum[js * 224 + (lane + 32 * (i + (js & 1))) % 224];
        sts64f(sb + TAB1_OFF + (lane + 32 * i) * 8, (__ldcg(p) + __ldcg(p + F_)) + (__ldcg(p + 2 * F_) + __ldcg(p + 3 * F_)), b1v[i]);
      }
      __syncwarp();
      if (lane == 0) mbar_arrive(BAR(B_TAB));
    }
  } else if (wg == 2) {
    const int w = warp - 8, ch = cid * 4 + w;
    uint2 par[6];
    {
      const int o = ch * NM_ + lane * 4;
      par[0] = __ldg(reinterpret_cast<const uint2*>(P.a_re + o)); par[1] = __ldg(reinterpret_cast<const uint2*>(P.a_im + o));
      par[2] = __ldg(reinterpret_cast<const uint2*>(P.b_re + o)); par[3] = __ldg(reinterpret_cast<const uint2*>(P.b_im + o));
      par[4] = __ldg(reinterpret_cast<const uint2*>(P.c_re + o)); par[5] = __ldg(reinterpret_cast<const uint2*>(P.c_im + o));
    }
    const float ldt = __bfloat162float(P.log_dt[ch]), dsk = __bfloat162float(P.dskip[ch]);
    cta_sync_and_cluster_arrive();
    asm volatile("setmaxnreg.inc.sync.aligned.u32 152;");
    float kacc[80];
    const float dt = bf_round(__expf(ldt));
    const uint64_t kda = mk_desc(sb + SSM_OFF, 16, 1024, 1), kdb = mk_desc(sb + SSM_OFF + 8192, 16, 1024, 1);
    float k2048 = 0.f;
#pragma unroll 1
    for (int b = 0; b < 4; b++) {
      float pv[6];
#pragma unroll
      for (int k = 0; k < 6; k++) { const uint32_t u = (b & 2) ? par[k].y : par[k].x; pv[k] = (b & 1) ? bf_hi(u) : bf_lo(u); }
      if (b >= 2) { WG_WAIT(1); bar_sync(2, 128); }
      k2048 += kgen_batch(sb + SSM_OFF + (b & 1) * KG_BUF, w, lane, dt, pv);
      if (b == 0) TS(20);
      if (b == 1) TS(21);
      if (b == 3) TS(22);
      fence_async_smem();
      bar_sync(2, 128);
      WG_FENCE();
#pragma unroll
      for (int kk = 0; kk < 4; kk++) wgmma_n160(kacc, kda + (b & 1) * (KG_BUF >> 4) + 2 * kk, kdb + (b & 1) * (KG_BUF >> 4) + 2 * kk, (b | kk) != 0);
      WG_COMMIT();
    }
    WG_WAIT(0);
    pin(kacc);
    bar_sync(2, 128);
    mbar_wait(BAR(B_LN), 0);
    TS(4);
    {
      const int g = lane >> 2, c = lane & 3;
      float kv[20];
      if (w == 0) {
#pragma unroll
        for (int i = 0; i < 20; i++) kv[i] = kacc[i];
      } else if (w == 1) {
#pragma unroll
        for (int i = 0; i < 20; i++) kv[i] = kacc[20 + i];
      } else if (w == 2) {
#pragma unroll
        for (int i = 0; i < 20; i++) kv[i] = kacc[40 + i];
      } else {
#pragma unroll
        for (int i = 0; i < 20; i++) kv[i] = kacc[60 + i];
      }
      if (lane == 0) kv[0] += dsk;
      k2048 = warp_sum(k2048);
      const uint32_t T = sb + KD_OFF + w * KD_CH;
#pragma unroll
      for (int hh = 0; hh < 2; hh++) {
        const int j = g + 8 * hh;
        sts32(T + 2 * (2 * c + 8 * j), pack2(kv[2 * hh], kv[2 * hh + 1]));
        sts32(T + 2 * (128 + 2 * c + 8 * j), pack2(kv[4 + 2 * hh], kv[5 + 2 * hh]));
        sts32(T + 2 * (256 + 64 * (c >> 1) + 2 * (c & 1) + 4 * j), pack2(kv[8 + 2 * hh], kv[9 + 2 * hh]));
        sts32(T + 2 * (384 + 32 * c + 2 * j), pack2(kv[12 + 2 * hh], kv[13 + 2 * hh]));
        const uint32_t pk = pack2(kv[16 + 2 * hh], kv[17 + 2 * hh]);
        sts16(T + 2 * (512 + 32 * c + j), pk & 0xffffu); sts16(T + 2 * (512 + 32 * c + 16 + j), pk >> 16);
      }
      if (lane == 0) sts16(T + 2 * 640, pack2(k2048, 0.f));
      __syncwarp();
      const uint32_t E = sb + KC_OFF + w * KC_CH + lane * 16, O = E + KC_COPY;
      auto P2 = [](uint32_t lo, uint32_t hi) { return __byte_perm(lo, hi, 0x5410); };
#pragma unroll
      for (int it = 0; it < 4; it++) {
        const int M = 256 - 32 * it - lane;
        const uint32_t a = lds16(T + 2 * (384 + M)), b = lds16(T + 2 * (383 + M)), t = (lane & 1) ? b : a;
        const uint32_t aa = P2(a, a), bb = P2(b, b);
        sts128(E + it * 512, aa, aa, P2(t, b), bb); sts128(O + it * 512, aa, P2(a, t), bb, bb);
      }
#pragma unroll
      for (int it = 4; it < 6; it++) {
        const int ia = 256 + 2 * (256 - 32 * it - lane);
        const uint32_t a = lds16(T + 2 * ia), b = lds16(T + 2 * ia - 2), cc = lds16(T + 2 * ia - 4);
        const uint32_t aa = P2(a, a), bb = P2(b, b), c2 = P2(cc, cc);
        sts128(E + it * 512, aa, P2(a, b), bb, c2); sts128(O + it * 512, aa, bb, P2(b, cc), c2);
      }
      {
        const int i0 = 128 + 4 * (64 - lane);
        const uint32_t v0 = lds16(T + 2 * i0), v1 = lds16(T + 2 * i0 - 2), v2 = lds16(T + 2 * i0 - 4), v3 = lds16(T + 2 * i0 - 6), v4 = lds16(T + 2 * i0 - 8);
        const uint32_t v22 = P2(v2, v2);
        sts128(E + 6 * 512, P2(v0, v0), P2(v1, v2), v22, P2(v3, v4)); sts128(O + 6 * 512, P2(v0, v1), v22, P2(v2, v3), P2(v4, v4));
      }
      {
        const int i0 = 8 * (32 - lane);
        uint32_t v[9];
#pragma unroll
        for (int k = 0; k < 9; k++) v[k] = lds16(T + 2 * (i0 - k));
        sts128(E + 7 * 512, P2(v[0], v[1]), P2(v[2], v[3]), P2(v[4], v[5]), P2(v[6], v[7]));
        sts128(O + 7 * 512, P2(v[1], v[2]), P2(v[3], v[4]), P2(v[5], v[6]), P2(v[7], v[8]));
      }
      if (lane < 4) { sts128(E + 8 * 512, lane == 0 ? lds16(T) : 0u, 0, 0, 0); sts128(O + 8 * 512, 0, 0, 0, 0); }
      __syncwarp();
      if (lane == 0) mbar_arrive(BAR(B_KRDY + w));
    }
    asm volatile("barrier.cluster.wait.acquire.aligned;" ::: "memory");
    mbar_wait(BAR(B_XT), 0);
    TS(5);
    {
      float acc[5][4];
      conv_mma<11, 15>(acc, sb, w, lane, 0, 8);
#pragma unroll
      for (int j = 0; j < 5; j++) conv_store(acc[j], ch, 11 + j, lane);
    }
    __syncwarp();
    if (lane == 0) mbar_arrive(BAR(B_CONV));
    TS(9);
  } else {
    const int ww = warp & 3, g = lane >> 2, c = lane & 3;
    {
      const int lrow = warp * 2 + (lane >> 4), sub = lane & 15;
      uint4 xr[4], wv[4];
      const __nv_bfloat16* p = P.x + (size_t)(cid * 16 + lrow) * D_ + sub * 8;
#pragma unroll
      for (int i = 0; i < 4; i++) xr[i] = ldg128(p + 128 * i);
      const int cq = cid < 112 ? cid : 0;
      const __nv_bfloat16* wp = P.w1 + (size_t)((cq & 3) * 128 + (tid >> 3)) * F_ + (cq >> 2) * 64 + (tid & 7) * 8;
#pragma unroll
      for (int r = 0; r < 4; r++) wv[r] = ldg128(wp + (size_t)r * 32 * F_);
      cta_sync_and_cluster_arrive();
      asm volatile("setmaxnreg.inc.sync.aligned.u32 160;");
      float f[32];
      float s = 0.f;
#pragma unroll
      for (int i = 0; i < 4; i++) {
        const uint32_t u[4] = {xr[i].x, xr[i].y, xr[i].z, xr[i].w};
#pragma unroll
        for (int k = 0; k < 4; k++) { f[8 * i + 2 * k] = bf_lo(u[k]); f[8 * i + 2 * k + 1] = bf_hi(u[k]); s += f[8 * i + 2 * k] + f[8 * i + 2 * k + 1]; }
      }
      TS(30);
      float mean = s * (1.f / 32.f), q0 = 0.f, q1 = 0.f;
#pragma unroll
      for (int k = 0; k < 32; k += 2) { const float d0 = f[k] - mean, d1 = f[k + 1] - mean; q0 = fmaf(d0, d0, q0); q1 = fmaf(d1, d1, q1); }
      float m2s = q0 + q1;
#pragma unroll
      for (int o = 1; o < 16; o <<= 1) {
        const float mo = __shfl_xor_sync(0xffffffffu, mean, o), qo = __shfl_xor_sync(0xffffffffu, m2s, o);
        const float dl = mean - mo;
        m2s = fmaf(dl * dl, 16.f * o, m2s + qo);
        mean = 0.5f * (mean + mo);
      }
      const float mb = bf_round(mean), s1 = bf_round(sqrtf(bf_round(bf_round(m2s * (1.f / D_)) + 1e-5f)));
      const float rs1 = 1.f / s1;
      if (rs1 != 123.f) TS(31);
      float sa = 0.f, sq0 = 0.f, sq1 = 0.f;
      const uint32_t ra = sb + LN_OFF + lrow * 1040 + sub * 16;
#pragma unroll
      for (int i = 0; i < 4; i++) {
        uint32_t o[4];
#pragma unroll
        for (int k = 0; k < 4; k++) {
          const uint32_t dd = pack2(f[8 * i + 2 * k] - mb, f[8 * i + 2 * k + 1] - mb);
          o[k] = pack2(bf_lo(dd) * rs1, bf_hi(dd) * rs1);
          const float a0 = bf_lo(o[k]), a1 = bf_hi(o[k]);
          sa += a0 + a1; sq0 = fmaf(a0, a0, sq0); sq1 = fmaf(a1, a1, sq1);
        }
        sts128(ra + 256 * i, o[0], o[1], o[2], o[3]);
      }
      float sq = sq0 + sq1;
#pragma unroll
      for (int o = 1; o < 16; o <<= 1) { sa += __shfl_xor_sync(0xffffffffu, sa, o); sq += __shfl_xor_sync(0xffffffffu, sq, o); }
      const float mean2 = sa * (1.f / D_), var2 = fmaxf(fmaf(-mean2, mean2, sq * (1.f / D_)), 0.f);
      const float m2b = bf_round(mean2), s2 = bf_round(sqrtf(bf_round(bf_round(var2) + 1e-5f)));
      const float rs2 = 1.f / s2;
      if (sub == 0) g_stats[cid * 16 + lrow] = make_float2(rs1 * rs2, -(mb * rs1 + m2b) * rs2);
      TS(27);
      float cs[8];
#pragma unroll
      for (int k = 0; k < 8; k++) cs[k] = 0.f;
#pragma unroll
      for (int r = 0; r < 4; r++) {
        const uint32_t u[4] = {wv[r].x, wv[r].y, wv[r].z, wv[r].w};
#pragma unroll
        for (int k = 0; k < 4; k++) { cs[2 * k] += bf_lo(u[k]); cs[2 * k + 1] += bf_hi(u[k]); }
      }
#pragma unroll
      for (int k = 0; k < 4; k++) { const bool up = lane & 8; const float snd = up ? cs[k] : cs[k + 4], kp = up ? cs[k + 4] : cs[k]; cs[k] = kp + __shfl_xor_sync(0xffffffffu, snd, 8); }
#pragma unroll
      for (int k = 0; k < 2; k++) { const bool up = lane & 16; const float snd = up ? cs[k] : cs[k + 2], kp = up ? cs[k + 2] : cs[k]; cs[k] = kp + __shfl_xor_sync(0xffffffffu, snd, 16); }
      sts64f(sb + WS_OFF + warp * 256 + ((lane & 7) * 8 + ((lane >> 3) & 1) * 4 + (lane >> 4) * 2) * 4, cs[0], cs[1]);
      TS(28);
      bar_sync(1, 256);
      if (lane == 0) mbar_arrive(BAR(B_CS));
      const int m = lane >> 3, rho = lane & 7;
      const int tok = 4 * (rho >> 1) + (rho & 1) + 2 * (m & 1);
      const int sw = (cid >> 2) & 1;
#pragma unroll
      for (int i = 0; i < 4; i++) {
        const int dg = warp * 4 + i;
        uint32_t r0, r1, r2, r3;
        ldsm4t(r0, r1, r2, r3, sb + LN_OFF + tok * 1040 + (dg * 16 + 8 * (m >> 1)) * 2);
        char* gp = reinterpret_cast<char*>(g_xnT + (size_t)(dg * 16 + g) * L_ + cid * 16) + (((c >> 1) ^ sw) << 4) + ((c & 1) << 3);
        *reinterpret_cast<uint2*>(gp) = make_uint2(r0, r1);
        *reinterpret_cast<uint2*>(gp + 8 * L_ * 2) = make_uint2(r2, r3);
      }
      __syncwarp();
      if (lane == 0) mbar_arrive(BAR(B_LN));
      TS(2);
    }
    {
      float accA[64], accB[48];
      uint32_t rempty;
      asm volatile("mapa.shared::cluster.u32 %0, %1, %2;" : "=r"(rempty) : "r"(BAR(B_EMPTY1)), "r"(rank ^ 1));
      asm volatile("barrier.cluster.wait.acquire.aligned;" ::: "memory");
#pragma unroll 1
      for (int kt = 0; kt < 16; kt++) {
        const int st = kt % S1_N;
        mbar_wait(BAR(B_FULL1 + st), (kt / S1_N) & 1);
        if (kt == 0) TS(18);
        if (kt == 6) TS(19);
        const uint64_t da = mk_desc(sb + st * S1_BYTES + wg * 4096, 16, 512, 2);
        const uint64_t db = mk_desc(sb + st * S1_BYTES + 8192, 4096, 1024, 1);
        WG_FENCE();
#pragma unroll
        for (int kk = 0; kk < 2; kk++) {
          wgmma_n128_tb(accA, da + 2 * kk, db + 128 * kk, (kt | kk) != 0);
          wgmma_n96_tb(accB, da + 2 * kk, db + 512 + 128 * kk, (kt | kk) != 0);
        }
        WG_COMMIT();
        WG_WAIT(1);
        if (kt > 0 && lane == 0) { mbar_arrive(BAR(B_EMPTY1 + (kt - 1) % S1_N)); mbar_arrive_remote_light(rempty + 8 * ((kt - 1) % S1_N)); }
      }
      WG_WAIT(0);
      pin(accA); pin(accB);
      if (lane == 0) { mbar_arrive(BAR(B_EMPTY1 + 15 % S1_N)); mbar_arrive_remote_light(rempty + 8 * (15 % S1_N)); }
      TS(11);
      bar_sync(1, 256);
      mbar_wait(BAR(B_TAB), 0);
      TS(23);
      const float2 st0 = lds64f(sb + STAT_OFF + (wg * 64 + ww * 16 + g) * 8), st1 = lds64f(sb + STAT_OFF + (wg * 64 + ww * 16 + g + 8) * 8);
      const int mi = lane >> 3, row = ww * 16 + 8 * (mi & 1) + (lane & 7);
      float4 tbl[28];
      tbl[0] = lds<float4>(sb + TAB1_OFF + 2 * c * 8); tbl[1] = lds<float4>(sb + TAB1_OFF + (8 + 2 * c) * 8);
      const uint32_t hrow = sb + wg * 28672 + row * 64;
      const int sw = (row >> 1) & 3;
      const uint32_t hrot = (js & 1) * 4096, hlast = (js & 1) ? 0 : 6 * 4096;
#pragma unroll
      for (int t = 0; t < 28; t += 2) {
        uint32_t r[4];
        if (t + 2 < 28) { tbl[t + 2] = lds<float4>(sb + TAB1_OFF + (8 * (t + 2) + 2 * c) * 8); tbl[t + 3] = lds<float4>(sb + TAB1_OFF + (8 * (t + 3) + 2 * c) * 8); }
#pragma unroll
        for (int u = 0; u < 2; u++) {
          const float4 tb = tbl[t + u];
          const float* a = (t + u) < 16 ? &accA[4 * (t + u)] : &accB[4 * (t + u - 16)];
          r[2 * u] = pack2(gelu_tanh(fmaf(a[0], st0.x, fmaf(st0.y, tb.x, tb.y))), gelu_tanh(fmaf(a[1], st0.x, fmaf(st0.y, tb.z, tb.w))));
          r[2 * u + 1] = pack2(gelu_tanh(fmaf(a[2], st1.x, fmaf(st1.y, tb.x, tb.y))), gelu_tanh(fmaf(a[3], st1.x, fmaf(st1.y, tb.z, tb.w))));
        }
        const int tt = t + (mi >> 1);
        stsm4(hrow + ((t >> 2) == 6 ? hlast : (t >> 2) * 4096 + hrot) + (((tt & 3) ^ sw) << 4), r[0], r[1], r[2], r[3]);
      }
      fence_async_smem();
      __syncwarp();
      if (lane == 0) mbar_arrive(BAR(B_HST + wg));
      TS(6);
    }
    mbar_wait(BAR(B_KRDY + ww), 0);
    mbar_wait(BAR(B_XT), 0);
    TS(24);
    {
      float acc[11][4];
      conv_mma<0, 10>(acc, sb, ww, lane, wg * 4, wg * 4 + 4);
      const uint32_t mb = sb + CM_OFF + (tid & 127) * 16;
      if (wg == 0) {
#pragma unroll
        for (int j = 6; j < 11; j++) sts128(mb + j * 2048, __float_as_uint(acc[j][0]), __float_as_uint(acc[j][1]), __float_as_uint(acc[j][2]), __float_as_uint(acc[j][3]));
      } else {
#pragma unroll
        for (int j = 0; j < 6; j++) sts128(mb + j * 2048, __float_as_uint(acc[j][0]), __float_as_uint(acc[j][1]), __float_as_uint(acc[j][2]), __float_as_uint(acc[j][3]));
      }
      bar_sync(5 + ww, 64);
      if (wg == 0) {
#pragma unroll
        for (int j = 0; j < 6; j++) {
          const float4 o = lds<float4>(mb + j * 2048);
          acc[j][0] += o.x; acc[j][1] += o.y; acc[j][2] += o.z; acc[j][3] += o.w;
          conv_store(acc[j], cid * 4 + ww, j, lane);
        }
      } else {
#pragma unroll
        for (int j = 6; j < 11; j++) {
          const float4 o = lds<float4>(mb + j * 2048);
          acc[j][0] += o.x; acc[j][1] += o.y; acc[j][2] += o.z; acc[j][3] += o.w;
          conv_store(acc[j], cid * 4 + ww, j, lane);
        }
      }
    }
    __syncwarp();
    if (lane == 0) mbar_arrive(BAR(B_CONV));
    TS(12);
    mbar_wait(BAR(B_CONV), 0);
    float acc[64];
#pragma unroll 1
    for (int it = 0; it < 14; it++) {
      const int s = it % S2_N;
      mbar_wait(BAR(B_FULL2 + s), (it / S2_N) & 1);
      if (it == 0) TS(25);
      if (it == 4) TS(26);
      const uint64_t da = mk_desc(sb + s2_off(s) + wg * 8192, 16, 1024, 1);
      const uint64_t db = mk_desc(sb + s2_off(s) + 16384, 8192, 1024, 1);
      WG_FENCE();
#pragma unroll
      for (int kk = 0; kk < 4; kk++) wgmma_n128_tb(acc, da + 2 * kk, db + 128 * kk, (it | kk) != 0);
      WG_COMMIT();
      WG_WAIT(1);
      if (it > 0 && lane == 0) mbar_arrive(BAR(B_EMPTY2 + (it - 1) % S2_N));
    }
    WG_WAIT(0);
    pin(acc);
    TS(13);
    float fin[32];
    mbar_wait_cluster(BAR(B_PFREE), 0);
    {
      uint32_t rbuf, rbar;
      asm volatile("mapa.shared::cluster.u32 %0, %1, %2;" : "=r"(rbuf) : "r"(sb + RED_OFF + tid * 16), "r"(rank ^ 1));
      asm volatile("mapa.shared::cluster.u32 %0, %1, %2;" : "=r"(rbar) : "r"(BAR(B_RED)), "r"(rank ^ 1));
      auto send = [&](int i, float a, float b, float cc, float d) {
        asm volatile("st.async.weak.shared::cluster.mbarrier::complete_tx::bytes.v4.f32 [%0], {%1,%2,%3,%4}, [%5];"
                     ::"r"(rbuf + i * 4096), "f"(a), "f"(b), "f"(cc), "f"(d), "r"(rbar) : "memory");
      };
      if (rank == 0) {
#pragma unroll
        for (int i = 0; i < 8; i++) send(i, acc[32 + 4 * i], acc[33 + 4 * i], acc[34 + 4 * i], acc[35 + 4 * i]);
#pragma unroll
        for (int i = 0; i < 32; i++) fin[i] = acc[i];
      } else {
#pragma unroll
        for (int i = 0; i < 8; i++) send(i, acc[4 * i], acc[4 * i + 1], acc[4 * i + 2], acc[4 * i + 3]);
#pragma unroll
        for (int i = 0; i < 32; i++) fin[i] = acc[32 + i];
      }
    }
    const uint32_t eb = sb + s2_off(14 % S2_N);
    mbar_wait(BAR(B_FULL2 + 14 % S2_N), (14 / S2_N) & 1);
    {
      const int mi = lane >> 3, r8 = lane & 7;
      const uint32_t xrow = eb + (wg * 64 + ww * 16 + 8 * (mi & 1) + r8) * 128;
      const uint32_t zrow = eb + 16384 + wg * 8192 + (8 * (mi >> 1) + r8) * 128 + (((2 * ww + (mi & 1)) ^ r8) << 4);
#pragma unroll
      for (int i = 0; i < 4; i++) {
        uint32_t xx[4], zz[4];
        ldsm4(xx[0], xx[1], xx[2], xx[3], xrow + (((2 * i + (mi >> 1)) ^ r8) << 4));
        ldsm4t(zz[0], zz[1], zz[2], zz[3], zrow + i * 2048);
#pragma unroll
        for (int k = 0; k < 4; k++) {
          const float2 bb = lds<float2>(sb + B2_OFF + (8 * (2 * i + (k >> 1)) + 2 * c) * 4);
          fin[8 * i + 2 * k] += bf_lo(xx[k]) + bf_lo(zz[k]) + bb.x;
          fin[8 * i + 2 * k + 1] += bf_hi(xx[k]) + bf_hi(zz[k]) + bb.y;
        }
      }
      mbar_wait_cluster(BAR(B_RED), 0);
#pragma unroll
      for (int i = 0; i < 4; i++) {
        const float4 p0 = lds128f(sb + RED_OFF + (2 * i) * 4096 + tid * 16), p1 = lds128f(sb + RED_OFF + (2 * i + 1) * 4096 + tid * 16);
        stsm4(xrow + (((2 * i + (mi >> 1)) ^ r8) << 4),
              pack2(fin[8 * i] + p0.x, fin[8 * i + 1] + p0.y), pack2(fin[8 * i + 2] + p0.z, fin[8 * i + 3] + p0.w),
              pack2(fin[8 * i + 4] + p1.x, fin[8 * i + 5] + p1.y), pack2(fin[8 * i + 6] + p1.z, fin[8 * i + 7] + p1.w));
      }
    }
    fence_async_smem();
    bar_sync(3 + wg, 128);
    if ((tid & 127) == 0) {
      tma_st2(&tmOut, cb * 128 + rank * 64, rb * 128 + wg * 64, eb + wg * 8192);
      bulk_commit();
      bulk_wait_read0();
    }
    TS(14);
  }
  TS_DUMP();
}

typedef CUresult (*EncodeFn)(CUtensorMap*, CUtensorMapDataType, cuuint32_t, void*, const cuuint64_t*, const cuuint64_t*,
                             const cuuint32_t*, const cuuint32_t*, CUtensorMapInterleave, CUtensorMapSwizzle,
                             CUtensorMapL2promotion, CUtensorMapFloatOOBfill);

CUtensorMap make_map(EncodeFn enc, const void* ptr, int rank, const cuuint64_t* dims, const cuuint64_t* strides,
                     const cuuint32_t* box, CUtensorMapSwizzle swz) {
  CUtensorMap m;
  const cuuint32_t es[3] = {1, 1, 1};
  enc(&m, CU_TENSOR_MAP_DATA_TYPE_BFLOAT16, rank, const_cast<void*>(ptr), dims, strides, box, es, CU_TENSOR_MAP_INTERLEAVE_NONE,
      swz, CU_TENSOR_MAP_L2_PROMOTION_L2_128B, CU_TENSOR_MAP_FLOAT_OOB_FILL_NONE);
  return m;
}

}

extern "C" void kernel_launch(void* const* d_in, const int* in_sizes, int n_in, void* d_out, int out_size) {
  (void)in_sizes; (void)n_in; (void)out_size;
  typedef const __nv_bfloat16* bp;
  Params P = {(bp)d_in[0], (bp)d_in[1], (bp)d_in[2], (bp)d_in[3], (bp)d_in[4], (bp)d_in[5], (bp)d_in[6], (bp)d_in[7],
              (bp)d_in[8], (bp)d_in[10], (bp)d_in[11], (bp)d_in[12], (bp)d_in[13]};
  void* fn = nullptr;
  cudaDriverEntryPointQueryResult qr;
  cudaGetDriverEntryPoint("cuTensorMapEncodeTiled", &fn, cudaEnableDefault, &qr);
  EncodeFn enc = (EncodeFn)fn;
  void *ph, *pz;
  cudaGetSymbolAddress(&ph, g_h);
  cudaGetSymbolAddress(&pz, g_zT);
  const cuuint64_t dX[2] = {D_, L_}, sX[1] = {D_ * 2};
  const cuuint32_t bXe[2] = {64, 128}, bOut[2] = {64, 64};
  const cuuint64_t dW1[3] = {64, D_, F_ / 64}, sW1[2] = {F_ * 2, 128}, dW1h[3] = {32, D_, F_ / 32}, sW1h[2] = {F_ * 2, 64};
  const cuuint32_t bW1g[3] = {64, 32, 2}, bW1s[3] = {64, 32, 1}, bX1[2] = {32, 128};
  const cuuint64_t dHs[3] = {32, L_, F_ / 32}, sHs[2] = {F_ * 2, 64};
  const cuuint32_t bHs[3] = {32, 64, 7};
  const cuuint64_t dHl[2] = {F_, L_}, sHl[1] = {F_ * 2};
  const cuuint32_t bHl[2] = {64, 128};
  const cuuint64_t dW2[3] = {64, F_, D_ / 64}, sW2[2] = {D_ * 2, 128};
  const cuuint32_t bW2[3] = {64, 64, 2};
  const cuuint64_t dZ[3] = {64, D_, L_ / 64}, sZ[2] = {L_ * 2, 128};
  const cuuint32_t bZ[3] = {64, 64, 2};
  CUtensorMap tmW1g = make_map(enc, P.w1, 3, dW1, sW1, bW1g, CU_TENSOR_MAP_SWIZZLE_128B);
  CUtensorMap tmW1s = make_map(enc, P.w1, 3, dW1, sW1, bW1s, CU_TENSOR_MAP_SWIZZLE_128B);
  CUtensorMap tmW1h = make_map(enc, P.w1, 3, dW1h, sW1h, bW1s, CU_TENSOR_MAP_SWIZZLE_128B);
  CUtensorMap tmHst = make_map(enc, ph, 3, dHs, sHs, bHs, CU_TENSOR_MAP_SWIZZLE_64B);
  CUtensorMap tmHld = make_map(enc, ph, 2, dHl, sHl, bHl, CU_TENSOR_MAP_SWIZZLE_128B);
  CUtensorMap tmW2 = make_map(enc, P.w2, 3, dW2, sW2, bW2, CU_TENSOR_MAP_SWIZZLE_128B);
  CUtensorMap tmXe = make_map(enc, P.x, 2, dX, sX, bXe, CU_TENSOR_MAP_SWIZZLE_128B);
  CUtensorMap tmX1 = make_map(enc, P.x, 2, dX, sX, bX1, CU_TENSOR_MAP_SWIZZLE_64B);
  CUtensorMap tmZ = make_map(enc, pz, 3, dZ, sZ, bZ, CU_TENSOR_MAP_SWIZZLE_128B);
  CUtensorMap tmOut = make_map(enc, d_out, 2, dX, sX, bOut, CU_TENSOR_MAP_SWIZZLE_128B);
  cudaFuncSetAttribute(fused_kernel, cudaFuncAttributeMaxDynamicSharedMemorySize, SMEM_BYTES);
  fused_kernel<<<NCTA, 512, SMEM_BYTES, cudaStreamPerThread>>>(tmW1g, tmW1s, tmW1h, tmHst, tmHld, tmW2, tmXe, tmX1, tmZ, tmOut, P);
}
```

```cpp
#include <cuda_runtime.h>
#include <cuda_bf16.h>
#include <cuda.h>
#include <stdint.h>

#define KCUT 0
namespace {

constexpr int L_ = 2048, D_ = 512, F_ = 1792, NM_ = 128;
constexpr int NCTA = 128;

constexpr uint32_t S1_BYTES = 24576, S1_N = 6;
constexpr uint32_t RING_BYTES = S1_BYTES * S1_N;
constexpr uint32_t S2_BYTES = 32768, S2_N = 4;
constexpr uint32_t XT_OFF = RING_BYTES;
constexpr uint32_t XT_CH = 4352;
constexpr uint32_t LN_OFF = XT_OFF;
constexpr uint32_t SSM_OFF = XT_OFF + 4 * XT_CH;
constexpr uint32_t KG_BUF = 28672;
constexpr uint32_t KG_HI = RING_BYTES - 2 * KG_BUF;
constexpr uint32_t KC_OFF = SSM_OFF;
constexpr uint32_t KC_COPY = 4160, KC_CH = 2 * KC_COPY;
constexpr uint32_t CM_OFF = SSM_OFF + 4 * KC_CH;
constexpr uint32_t CS_OFF = CM_OFF;
constexpr uint32_t KD_OFF = CM_OFF + 16384;
constexpr uint32_t KD_CH = 1312;
constexpr uint32_t RED_OFF = XT_OFF;
constexpr uint32_t BASE_OFF = RED_OFF + 32768;
constexpr uint32_t ZT_OFF = BASE_OFF + 16384;
constexpr uint32_t ST_OFF = 0;
constexpr uint32_t AZ_OFF = SSM_OFF + 2 * KG_BUF;
constexpr uint32_t AX_OFF = AZ_OFF + 2048;
constexpr uint32_t BX_OFF = AX_OFF + 2048;
constexpr uint32_t WS_OFF = AX_OFF;
constexpr uint32_t SC_OFF = BX_OFF + 3584;
constexpr uint32_t K2_OFF = SC_OFF + 512;
constexpr uint32_t BAR_OFF = K2_OFF + 64;
constexpr uint32_t EPOCH_OFF = BAR_OFF + 320;
constexpr uint32_t SMEM_BYTES = EPOCH_OFF + 16 + 128 + 512;
static_assert(KD_OFF + 4 * KD_CH <= AZ_OFF && ZT_OFF + 16384 <= AZ_OFF && (ZT_OFF & 1023) == 0 && (SSM_OFF & 1023) == 0, "smem");
static_assert(SMEM_BYTES <= 232448, "smem");

enum { B_FULL1 = 0, B_EMPTY1 = 6, B_FULL2 = 12, B_EMPTY2 = 16, B_HST = 20  , B_BASE = 22, B_KG = 26, B_LN = 24, B_CONV = 25,
       B_TAB = 23, B_HFREE = 27, B_KRDY = 28  , B_XT = 32, B_PFREE = 33, B_EPI = 34, B_XR = 35, B_CW = 36, B_RED = 37 };

__device__ __align__(1024) __nv_bfloat16 g_h[L_ * F_];
__device__ __align__(1024) __nv_bfloat16 g_xnT[D_ * L_];
__device__ __align__(1024) __nv_bfloat16 g_zT[D_ * L_];
__device__ __align__(256) uint4 g_stats[L_];
__device__ __align__(256) uint2 g_w1sum[F_ * 4];
__device__ __align__(256) unsigned g_cnt[64 * 32];
enum { C_LN = 32, C_Z = 64, C_H = 96   };
#define TS(i)
#define TS_DUMP()
#define TS0(i)
#define DBG(b) 0
#define TS_G(v)

__device__ __forceinline__ uint32_t smem_u32(const void* p) { return (uint32_t)__cvta_generic_to_shared(p); }
__device__ __forceinline__ void mbar_init(uint32_t bar, uint32_t cnt) {
  asm volatile("mbarrier.init.shared::cta.b64 [%0], %1;" ::"r"(bar), "r"(cnt) : "memory");
}
__device__ __forceinline__ void mbar_arrive(uint32_t bar) {
  asm volatile("mbarrier.arrive.shared::cta.b64 _, [%0];" ::"r"(bar) : "memory");
}
__device__ __forceinline__ void mbar_arrive_remote_light(uint32_t bar_cluster) {
  asm volatile("mbarrier.arrive.shared::cluster.b64 _, [%0];" ::"r"(bar_cluster) : "memory");
}
__device__ __forceinline__ void mbar_expect(uint32_t bar, uint32_t bytes) {
  asm volatile("mbarrier.arrive.expect_tx.shared::cta.b64 _, [%0], %1;" ::"r"(bar), "r"(bytes) : "memory");
}
#define MBAR_WAIT_BODY(SEM)                                                                                      \
  asm volatile("{\n.reg .pred p;\nW:\nmbarrier.try_wait.parity" SEM ".shared::cta.b64 p, [%0], %1, 1000000;\n@!p bra W;\n}" \
               ::"r"(bar), "r"(parity) : "memory");
__device__ __forceinline__ void mbar_wait(uint32_t bar, uint32_t parity) { MBAR_WAIT_BODY("") }
__device__ __forceinline__ void mbar_wait_cluster(uint32_t bar, uint32_t parity) { MBAR_WAIT_BODY(".acquire.cluster") }
__device__ __forceinline__ bool elect() {
  uint32_t p;
  asm volatile("{\n.reg .pred p;\nelect.sync _|p, 0xffffffff;\nselp.u32 %0, 1, 0, p;\n}" : "=r"(p));
  return p != 0;
}
__device__ __forceinline__ void bar_sync(int id, int n) { asm volatile("bar.sync %0, %1;" ::"r"(id), "r"(n) : "memory"); }
__device__ __forceinline__ void fence_async_smem() { asm volatile("fence.proxy.async.shared::cta;" ::: "memory"); }
__device__ __forceinline__ void fence_async_global() { asm volatile("fence.proxy.async.global;" ::: "memory"); }
__device__ __forceinline__ void tma_ld2(uint32_t dst, const CUtensorMap* m, int c0, int c1, uint32_t bar) {
  asm volatile("cp.async.bulk.tensor.2d.shared::cluster.global.mbarrier::complete_tx::bytes [%0], [%1, {%3, %4}], [%2];"
               ::"r"(dst), "l"(m), "r"(bar), "r"(c0), "r"(c1) : "memory");
}
__device__ __forceinline__ void tma_ld3(uint32_t dst, const CUtensorMap* m, int c0, int c1, int c2, uint32_t bar) {
  asm volatile("cp.async.bulk.tensor.3d.shared::cluster.global.mbarrier::complete_tx::bytes [%0], [%1, {%3, %4, %5}], [%2];"
               ::"r"(dst), "l"(m), "r"(bar), "r"(c0), "r"(c1), "r"(c2) : "memory");
}
__device__ __forceinline__ void tma_ld3_mc(uint32_t dst, const CUtensorMap* m, int c0, int c1, int c2, uint32_t bar) {
  asm volatile("cp.async.bulk.tensor.3d.shared::cluster.global.mbarrier::complete_tx::bytes.multicast::cluster [%0], [%1, {%3, %4, %5}], [%2], %6;"
               ::"r"(dst), "l"(m), "r"(bar), "r"(c0), "r"(c1), "r"(c2), "h"((uint16_t)3) : "memory");
}
__device__ __forceinline__ void tma_st3(const CUtensorMap* m, int c0, int c1, int c2, uint32_t src) {
  asm volatile("cp.async.bulk.tensor.3d.global.shared::cta.bulk_group [%0, {%2, %3, %4}], [%1];"
               ::"l"(m), "r"(src), "r"(c0), "r"(c1), "r"(c2) : "memory");
}
__device__ __forceinline__ void bulk_ld(uint32_t dst, const void* src, uint32_t bytes, uint32_t bar) {
  asm volatile("cp.async.bulk.shared::cluster.global.mbarrier::complete_tx::bytes [%0], [%1], %2, [%3];"
               ::"r"(dst), "l"(src), "r"(bytes), "r"(bar) : "memory");
}
__device__ __forceinline__ void bulk_commit() { asm volatile("cp.async.bulk.commit_group;" ::: "memory"); }
__device__ __forceinline__ void bulk_wait_read0() { asm volatile("cp.async.bulk.wait_group.read 0;" ::: "memory"); }
__device__ __forceinline__ void bulk_wait0() { asm volatile("cp.async.bulk.wait_group 0;" ::: "memory"); }
__device__ __forceinline__ void prefetch_map(const CUtensorMap* m) { asm volatile("prefetch.tensormap [%0];" ::"l"(m) : "memory"); }
__device__ __forceinline__ void l2_prefetch(const void* p, uint32_t bytes) {
  asm volatile("cp.async.bulk.prefetch.L2.global [%0], %1;" ::"l"(p), "r"(bytes) : "memory");
}
__device__ __forceinline__ void signal_done(unsigned* p) { asm volatile("red.relaxed.gpu.global.add.u32 [%0], 1;" ::"l"(p) : "memory"); }
__device__ __forceinline__ void st_tagged(void* p, float v, uint32_t tag) {
  asm volatile("st.relaxed.gpu.global.b64 [%0], %1;" ::"l"(p), "l"((uint64_t)__float_as_uint(v) | ((uint64_t)tag << 32)) : "memory");
}
__device__ __forceinline__ uint4 ld_tagged2(const void* p) {
  uint64_t a, b;
  asm volatile("ld.relaxed.gpu.global.v2.b64 {%0,%1}, [%2];" : "=l"(a), "=l"(b) : "l"(p) : "memory");
  return make_uint4((uint32_t)a, (uint32_t)(a >> 32), (uint32_t)b, (uint32_t)(b >> 32));
}
__device__ __forceinline__ void wait_gpu(const unsigned* p, unsigned target) {
#pragma unroll 1
  for (int it = 0; it < (1 << 22); it++) {
    unsigned v;
    asm volatile("ld.relaxed.gpu.global.u32 %0, [%1];" : "=r"(v) : "l"(p) : "memory");
    if ((int)(v - target) >= 0) return;
    __nanosleep(64);
  }
  __trap();
}
__device__ __forceinline__ uint64_t mk_desc(uint32_t addr, uint32_t lbo, uint32_t sbo, uint32_t swz) {
  return (uint64_t)((addr & 0x3FFFF) >> 4) | ((uint64_t)(lbo >> 4) << 16) | ((uint64_t)(sbo >> 4) << 32) | ((uint64_t)swz << 62);
}
#define WG_FENCE() asm volatile("wgmma.fence.sync.aligned;" ::: "memory")
#define WG_COMMIT() asm volatile("wgmma.commit_group.sync.aligned;" ::: "memory")
#define WG_WAIT(n) asm volatile("wgmma.wait_group.sync.aligned %0;" ::"n"(n) : "memory")
template <int N> __device__ __forceinline__ void pin(float (&d)[N]) {
#pragma unroll
  for (int i = 0; i < N; i++) asm volatile("" : "+f"(d[i])::"memory");
}
__device__ __forceinline__ void wgmma_n96_tb(float (&d)[48], uint64_t da, uint64_t db, int scale_d) {
  asm volatile("{\n.reg .pred p;\nsetp.ne.b32 p, %50, 0;\n"
    "wgmma.mma_async.sync.aligned.m64n96k16.f32.bf16.bf16 {%0, %1, %2, %3, %4, %5, %6, %7, %8, %9, %10, %11, %12, %13, %14, %15, %16, %17, %18, %19, %20, %21, %22, %23, %24, %25, %26, %27, %28, %29, %30, %31, %32, %33, %34, %35, %36, %37, %38, %39, %40, %41, %42, %43, %44, %45, %46, %47}, %48, %49, p, 1, 1, 0, 1;\n}"
   : "+f"(d[0]), "+f"(d[1]), "+f"(d[2]), "+f"(d[3]), "+f"(d[4]), "+f"(d[5]), "+f"(d[6]), "+f"(d[7]), "+f"(d[8]), "+f"(d[9]), "+f"(d[10]), "+f"(d[11]), "+f"(d[12]), "+f"(d[13]), "+f"(d[14]), "+f"(d[15]), "+f"(d[16]), "+f"(d[17]), "+f"(d[18]), "+f"(d[19]), "+f"(d[20]), "+f"(d[21]), "+f"(d[22]), "+f"(d[23]), "+f"(d[24]), "+f"(d[25]), "+f"(d[26]), "+f"(d[27]), "+f"(d[28]), "+f"(d[29]), "+f"(d[30]), "+f"(d[31]), "+f"(d[32]), "+f"(d[33]), "+f"(d[34]), "+f"(d[35]), "+f"(d[36]), "+f"(d[37]), "+f"(d[38]), "+f"(d[39]), "+f"(d[40]), "+f"(d[41]), "+f"(d[42]), "+f"(d[43]), "+f"(d[44]), "+f"(d[45]), "+f"(d[46]), "+f"(d[47])
   : "l"(da), "l"(db), "r"(scale_d));
}
__device__ __forceinline__ void wgmma_n128_tb(float (&d)[64], uint64_t da, uint64_t db, int scale_d) {
  asm volatile("{\n.reg .pred p;\nsetp.ne.b32 p, %66, 0;\n"
    "wgmma.mma_async.sync.aligned.m64n128k16.f32.bf16.bf16 {%0, %1, %2, %3, %4, %5, %6, %7, %8, %9, %10, %11, %12, %13, %14, %15, %16, %17, %18, %19, %20, %21, %22, %23, %24, %25, %26, %27, %28, %29, %30, %31, %32, %33, %34, %35, %36, %37, %38, %39, %40, %41, %42, %43, %44, %45, %46, %47, %48, %49, %50, %51, %52, %53, %54, %55, %56, %57, %58, %59, %60, %61, %62, %63}, %64, %65, p, 1, 1, 0, 1;\n}"
   : "+f"(d[0]), "+f"(d[1]), "+f"(d[2]), "+f"(d[3]), "+f"(d[4]), "+f"(d[5]), "+f"(d[6]), "+f"(d[7]), "+f"(d[8]), "+f"(d[9]), "+f"(d[10]), "+f"(d[11]), "+f"(d[12]), "+f"(d[13]), "+f"(d[14]), "+f"(d[15]), "+f"(d[16]), "+f"(d[17]), "+f"(d[18]), "+f"(d[19]), "+f"(d[20]), "+f"(d[21]), "+f"(d[22]), "+f"(d[23]), "+f"(d[24]), "+f"(d[25]), "+f"(d[26]), "+f"(d[27]), "+f"(d[28]), "+f"(d[29]), "+f"(d[30]), "+f"(d[31]), "+f"(d[32]), "+f"(d[33]), "+f"(d[34]), "+f"(d[35]), "+f"(d[36]), "+f"(d[37]), "+f"(d[38]), "+f"(d[39]), "+f"(d[40]), "+f"(d[41]), "+f"(d[42]), "+f"(d[43]), "+f"(d[44]), "+f"(d[45]), "+f"(d[46]), "+f"(d[47]), "+f"(d[48]), "+f"(d[49]), "+f"(d[50]), "+f"(d[51]), "+f"(d[52]), "+f"(d[53]), "+f"(d[54]), "+f"(d[55]), "+f"(d[56]), "+f"(d[57]), "+f"(d[58]), "+f"(d[59]), "+f"(d[60]), "+f"(d[61]), "+f"(d[62]), "+f"(d[63])
   : "l"(da), "l"(db), "r"(scale_d));
}
__device__ __forceinline__ void wgmma_n96(float (&d)[48], uint64_t da, uint64_t db, int scale_d) {
  asm volatile("{\n.reg .pred p;\nsetp.ne.b32 p, %50, 0;\n"
    "wgmma.mma_async.sync.aligned.m64n96k16.f32.bf16.bf16 {%0, %1, %2, %3, %4, %5, %6, %7, %8, %9, %10, %11, %12, %13, %14, %15, %16, %17, %18, %19, %20, %21, %22, %23, %24, %25, %26, %27, %28, %29, %30, %31, %32, %33, %34, %35, %36, %37, %38, %39, %40, %41, %42, %43, %44, %45, %46, %47}, %48, %49, p, 1, 1, 0, 0;\n}"
   : "+f"(d[0]), "+f"(d[1]), "+f"(d[2]), "+f"(d[3]), "+f"(d[4]), "+f"(d[5]), "+f"(d[6]), "+f"(d[7]), "+f"(d[8]), "+f"(d[9]), "+f"(d[10]), "+f"(d[11]), "+f"(d[12]), "+f"(d[13]), "+f"(d[14]), "+f"(d[15]), "+f"(d[16]), "+f"(d[17]), "+f"(d[18]), "+f"(d[19]), "+f"(d[20]), "+f"(d[21]), "+f"(d[22]), "+f"(d[23]), "+f"(d[24]), "+f"(d[25]), "+f"(d[26]), "+f"(d[27]), "+f"(d[28]), "+f"(d[29]), "+f"(d[30]), "+f"(d[31]), "+f"(d[32]), "+f"(d[33]), "+f"(d[34]), "+f"(d[35]), "+f"(d[36]), "+f"(d[37]), "+f"(d[38]), "+f"(d[39]), "+f"(d[40]), "+f"(d[41]), "+f"(d[42]), "+f"(d[43]), "+f"(d[44]), "+f"(d[45]), "+f"(d[46]), "+f"(d[47])
   : "l"(da), "l"(db), "r"(scale_d));
}
__device__ __forceinline__ void wgmma_n128(float (&d)[64], uint64_t da, uint64_t db, int scale_d) {
  asm volatile("{\n.reg .pred p;\nsetp.ne.b32 p, %66, 0;\n"
    "wgmma.mma_async.sync.aligned.m64n128k16.f32.bf16.bf16 {%0, %1, %2, %3, %4, %5, %6, %7, %8, %9, %10, %11, %12, %13, %14, %15, %16, %17, %18, %19, %20, %21, %22, %23, %24, %25, %26, %27, %28, %29, %30, %31, %32, %33, %34, %35, %36, %37, %38, %39, %40, %41, %42, %43, %44, %45, %46, %47, %48, %49, %50, %51, %52, %53, %54, %55, %56, %57, %58, %59, %60, %61, %62, %63}, %64, %65, p, 1, 1, 0, 0;\n}"
   : "+f"(d[0]), "+f"(d[1]), "+f"(d[2]), "+f"(d[3]), "+f"(d[4]), "+f"(d[5]), "+f"(d[6]), "+f"(d[7]), "+f"(d[8]), "+f"(d[9]), "+f"(d[10]), "+f"(d[11]), "+f"(d[12]), "+f"(d[13]), "+f"(d[14]), "+f"(d[15]), "+f"(d[16]), "+f"(d[17]), "+f"(d[18]), "+f"(d[19]), "+f"(d[20]), "+f"(d[21]), "+f"(d[22]), "+f"(d[23]), "+f"(d[24]), "+f"(d[25]), "+f"(d[26]), "+f"(d[27]), "+f"(d[28]), "+f"(d[29]), "+f"(d[30]), "+f"(d[31]), "+f"(d[32]), "+f"(d[33]), "+f"(d[34]), "+f"(d[35]), "+f"(d[36]), "+f"(d[37]), "+f"(d[38]), "+f"(d[39]), "+f"(d[40]), "+f"(d[41]), "+f"(d[42]), "+f"(d[43]), "+f"(d[44]), "+f"(d[45]), "+f"(d[46]), "+f"(d[47]), "+f"(d[48]), "+f"(d[49]), "+f"(d[50]), "+f"(d[51]), "+f"(d[52]), "+f"(d[53]), "+f"(d[54]), "+f"(d[55]), "+f"(d[56]), "+f"(d[57]), "+f"(d[58]), "+f"(d[59]), "+f"(d[60]), "+f"(d[61]), "+f"(d[62]), "+f"(d[63])
   : "l"(da), "l"(db), "r"(scale_d));
}
__device__ __forceinline__ void wgmma_n48(float (&d)[24], uint64_t da, uint64_t db, int scale_d) {
  asm volatile("{\n.reg .pred p;\nsetp.ne.b32 p, %26, 0;\n"
    "wgmma.mma_async.sync.aligned.m64n48k16.f32.bf16.bf16 {%0, %1, %2, %3, %4, %5, %6, %7, %8, %9, %10, %11, %12, %13, %14, %15, %16, %17, %18, %19, %20, %21, %22, %23}, %24, %25, p, 1, 1, 0, 0;\n}"
   : "+f"(d[0]), "+f"(d[1]), "+f"(d[2]), "+f"(d[3]), "+f"(d[4]), "+f"(d[5]), "+f"(d[6]), "+f"(d[7]), "+f"(d[8]), "+f"(d[9]), "+f"(d[10]), "+f"(d[11]), "+f"(d[12]), "+f"(d[13]), "+f"(d[14]), "+f"(d[15]), "+f"(d[16]), "+f"(d[17]), "+f"(d[18]), "+f"(d[19]), "+f"(d[20]), "+f"(d[21]), "+f"(d[22]), "+f"(d[23])
   : "l"(da), "l"(db), "r"(scale_d));
}

__device__ __forceinline__ void mma16816(float* d, uint32_t a0, uint32_t a1, uint32_t a2, uint32_t a3, uint32_t b0, uint32_t b1) {
  asm("mma.sync.aligned.m16n8k16.row.col.f32.bf16.bf16.f32 {%0,%1,%2,%3}, {%4,%5,%6,%7}, {%8,%9}, {%0,%1,%2,%3};"
               : "+f"(d[0]), "+f"(d[1]), "+f"(d[2]), "+f"(d[3]) : "r"(a0), "r"(a1), "r"(a2), "r"(a3), "r"(b0), "r"(b1));
}
__device__ __forceinline__ void ldsm4(uint32_t& r0, uint32_t& r1, uint32_t& r2, uint32_t& r3, uint32_t addr) {
  asm volatile("ldmatrix.sync.aligned.m8n8.x4.shared.b16 {%0,%1,%2,%3}, [%4];" : "=r"(r0), "=r"(r1), "=r"(r2), "=r"(r3) : "r"(addr) : "memory");
}
__device__ __forceinline__ void ldsm4t(uint32_t& r0, uint32_t& r1, uint32_t& r2, uint32_t& r3, uint32_t addr) {
  asm volatile("ldmatrix.sync.aligned.m8n8.x4.trans.shared.b16 {%0,%1,%2,%3}, [%4];" : "=r"(r0), "=r"(r1), "=r"(r2), "=r"(r3) : "r"(addr) : "memory");
}
__device__ __forceinline__ void stsm4(uint32_t addr, uint32_t r0, uint32_t r1, uint32_t r2, uint32_t r3) {
  asm volatile("stmatrix.sync.aligned.m8n8.x4.shared.b16 [%0], {%1,%2,%3,%4};" ::"r"(addr), "r"(r0), "r"(r1), "r"(r2), "r"(r3) : "memory");
}
__device__ __forceinline__ uint32_t lds16(uint32_t a) { uint16_t v; asm volatile("ld.shared.u16 %0, [%1];" : "=h"(v) : "r"(a) : "memory"); return v; }
template <typename T> __device__ __forceinline__ T lds(uint32_t a) {
  return *reinterpret_cast<const T*>(__cvta_shared_to_generic(a));
}
__device__ __forceinline__ void sts32(uint32_t a, uint32_t v) { asm volatile("st.shared.u32 [%0], %1;" ::"r"(a), "r"(v) : "memory"); }
__device__ __forceinline__ void sts16(uint32_t a, uint32_t v) { asm volatile("st.shared.u16 [%0], %1;" ::"r"(a), "h"((uint16_t)v) : "memory"); }
__device__ __forceinline__ void sts128(uint32_t a, uint32_t x, uint32_t y, uint32_t z, uint32_t w) {
  asm volatile("st.shared.v4.u32 [%0], {%1,%2,%3,%4};" ::"r"(a), "r"(x), "r"(y), "r"(z), "r"(w) : "memory");
}
__device__ __forceinline__ void sts128f(uint32_t a, float x, float y, float z, float w) {
  asm volatile("st.shared.v4.f32 [%0], {%1,%2,%3,%4};" ::"r"(a), "f"(x), "f"(y), "f"(z), "f"(w) : "memory");
}
__device__ __forceinline__ uint32_t pack2(float lo, float hi) {
  uint32_t r; asm("cvt.rn.bf16x2.f32 %0, %1, %2;" : "=r"(r) : "f"(hi), "f"(lo)); return r;
}
__device__ __forceinline__ float bf_lo(uint32_t v) { return __uint_as_float(v << 16); }
__device__ __forceinline__ float bf_hi(uint32_t v) { return __uint_as_float(v & 0xffff0000u); }
__device__ __forceinline__ float bf_round(float v) { return bf_lo(pack2(v, 0.f)); }
__device__ __forceinline__ float sqrt_approx(float v) { float r; asm("sqrt.approx.ftz.f32 %0, %1;" : "=f"(r) : "f"(v)); return r; }
__device__ __forceinline__ float rcp_approx(float v) { float r; asm("rcp.approx.ftz.f32 %0, %1;" : "=f"(r) : "f"(v)); return r; }
__device__ __forceinline__ float warp_sum(float v) {
#pragma unroll
  for (int o = 16; o > 0; o >>= 1) v += __shfl_xor_sync(0xffffffffu, v, o);
  return v;
}
struct cf { float r, i; };
__device__ __forceinline__ cf cmul(cf a, cf b) { return {fmaf(a.r, b.r, -a.i * b.i), fmaf(a.r, b.i, a.i * b.r)}; }
__device__ __forceinline__ cf csqr(cf a) { return {fmaf(a.r, a.r, -a.i * a.i), (a.r + a.r) * a.i}; }
__device__ __forceinline__ cf cexp_at(float lr2, float li, float x) {
  float m; asm("ex2.approx.ftz.f32 %0, %1;" : "=f"(m) : "f"(lr2 * x));
  return {m * __cosf(li * x), m * __sinf(li * x)};
}
constexpr float GK = 2.f * 0.7978845608028654f;
__device__ __forceinline__ uint32_t gelu2(float y0, float y1) {
  uint32_t r;
  asm("{\n.reg .b32 y, z, t;\ncvt.rn.bf16x2.f32 y, %2, %1;\nmul.rn.bf16x2 z, y, y;\nmul.rn.bf16x2 z, z, %3;\n"
      "fma.rn.bf16x2 z, z, y, y;\ntanh.approx.bf16x2 t, z;\nfma.rn.bf16x2 %0, y, t, y;\n}"
      : "=r"(r) : "f"(y0), "f"(y1), "r"(0x3d903d90u));
  return r;
}

template <bool SQ>
__device__ __forceinline__ void conv_mma(float (&acc)[8][4], uint32_t kc, uint32_t xt, int lane) {
  const int g = lane >> 2, c = lane & 3;
#pragma unroll
  for (int j = 0; j < 8; j++) { acc[j][0] = acc[j][1] = acc[j][2] = acc[j][3] = 0.f; }
  uint32_t ka = kc + (g & 1) * KC_COPY + 4 * (1024 - ((g + 1) >> 1) + c);
  const uint32_t xbase = xt + 256 + (lane >> 4) * 256;
  int rr = lane & 7;
#pragma unroll 1
  for (int rho = 0; rho < 8; rho++, rr--, ka -= 32) {
    uint32_t X[8][2];
    const uint32_t xa = xbase + rr * 32 + ((((lane >> 3) ^ (rr >> 2)) & 1) << 4);
#pragma unroll
    for (int i = 3; i >= 0; i--) ldsm4(X[2 * i][0], X[2 * i][1], X[2 * i + 1][0], X[2 * i + 1][1], xa + i * 512);
#pragma unroll
    for (int kap = (SQ ? 1 : 0); kap < (SQ ? 16 : 8); kap++) {
      const uint32_t a0 = lds<uint32_t>(ka - 256 * kap), a1 = lds<uint32_t>(ka - 256 * kap - 16), a2 = lds<uint32_t>(ka - 256 * kap + 16);
      uint32_t a3;
      asm volatile("prmt.b32 %0, %1, %1, 0x3210;" : "=r"(a3) : "r"(a0));
#pragma unroll
      for (int j = 0; j < 8; j++) {
        const int jx = (SQ ? j + 8 : j) - kap;
        if (jx >= 0 && jx < 8) mma16816(acc[j], a0, a1, a2, a3, X[jx][0], X[jx][1]);
      }
    }
  }
}

struct Params {
  const __nv_bfloat16 *x, *a_re, *a_im, *b_re, *b_im, *c_re, *c_im, *log_dt, *dskip, *w1, *b1, *w2, *b2;
};

__global__ void __cluster_dims__(2, 1, 1) __launch_bounds__(512, 1)
fused_kernel(const __grid_constant__ CUtensorMap tmX1, const __grid_constant__ CUtensorMap tmW1s, const __grid_constant__ CUtensorMap tmW1h,
             const __grid_constant__ CUtensorMap tmHs, const __grid_constant__ CUtensorMap tmHh, const __grid_constant__ CUtensorMap tmHld,
             const __grid_constant__ CUtensorMap tmW2, const __grid_constant__ CUtensorMap tmXe, const __grid_constant__ CUtensorMap tmZ,
             const __grid_constant__ CUtensorMap tmOut, const __grid_constant__ CUtensorMap tmW1c, const __grid_constant__ CUtensorMap tmXT,
             const Params P) {
  extern __shared__ __align__(1024) uint8_t smem_raw[];
  const uint32_t sb = smem_u32(smem_raw);
  auto BAR = [&](int i) { return sb + BAR_OFF + 8u * i; };
  const int tid = threadIdx.x, warp = tid >> 5, lane = tid & 31, wg = tid >> 7, ww = warp & 3, g = lane >> 2, c = lane & 3;
  const int cl = blockIdx.x >> 1, rank = blockIdx.x & 1, q7 = ((cl - 36) * 37) >> 8;
  const int grp = cl < 4 ? 0 : cl < 36 ? (cl - 4) & 7 : cl - 35 - 7 * q7, pp = cl < 4 ? 4 + cl : cl < 36 ? (cl - 4) >> 3 : 4 + q7;
  const int rb1 = 2 * grp + rank, js = pp;
  const int rb = 2 * grp + (pp >> 2), cb = pp & 3;
  const int cid = rb1 * 8 + js;
  const int w1g = 7 * (js >> 1) + 4 * (js & 1), w1h = 14 * (js >> 1) + 6 + (js & 1);
  const int ch = cid * 4 + ww, oc = cb * 128 + rank * 64;
  TS_G(_g0);
  TS(0);
  const int po = ch * NM_ + wg * 32 + lane;
  auto ldu16 = [](const __nv_bfloat16* p) { return (uint32_t)__ldg(reinterpret_cast<const unsigned short*>(p)); };
  uint32_t pr[7] = {ldu16(P.a_re + po), ldu16(P.a_im + po), ldu16(P.b_re + po), ldu16(P.b_im + po), ldu16(P.c_re + po), ldu16(P.c_im + po), ldu16(P.log_dt + ch)};
  unsigned ep;
  asm volatile("ld.relaxed.gpu.global.u32 %0, [%1];" : "=r"(ep) : "l"(&g_cnt[C_Z]) : "memory");
  if (warp == 12) {
    if (elect()) {
      prefetch_map(&tmX1); prefetch_map(&tmW1s); prefetch_map(&tmW1h);
      for (int i = 0; i < (int)S1_N; i++) mbar_init(BAR(B_FULL1 + i), 1);
    }
    __syncwarp();
  }
  if (warp == 13) {
    if (elect()) {
      for (int i = 0; i < (int)S1_N; i++) mbar_init(BAR(B_EMPTY1 + i), 16);
      for (int i = 0; i < (int)S2_N; i++) { mbar_init(BAR(B_FULL2 + i), 1); mbar_init(BAR(B_EMPTY2 + i), 8); }
    }
    __syncwarp();
  }
  if (warp == 14) {
    if (elect()) {
      mbar_init(BAR(B_HST), 8); mbar_init(BAR(B_BASE), 4);
      mbar_init(BAR(B_KG), 1); mbar_init(BAR(B_TAB), 4); mbar_init(BAR(B_LN), 9); mbar_init(BAR(B_CONV), 12);
      for (int i = B_HFREE; i <= B_RED; i++) mbar_init(BAR(i), 1);
      mbar_expect(BAR(B_RED), 32768);
    }
    __syncwarp();
  }
  asm volatile("fence.mbarrier_init.release.cluster;" ::: "memory");
  asm volatile("barrier.cluster.arrive.relaxed.aligned;" ::: "memory");
  const uint32_t sh16 = 16 + (uint32_t)(clock64() >> 63);
  TS0(0);
  const int zero = (pr[6] << (sh16 - 16)) >> 16;
    auto load_stage1 = [&](int kt, int st) {
      const uint32_t dst = sb + st * S1_BYTES, bar = BAR(B_FULL1 + st);
      mbar_expect(bar, S1_BYTES);
      tma_ld2(dst, &tmX1, kt * 32, rb1 * 128, bar);
      tma_ld3_mc(dst + 8192 + rank * 8192, &tmW1s, 0, kt * 32, w1g + 2 * rank, bar);
      tma_ld3_mc(dst + 12288 + rank * 8192, rank ? &tmW1h : &tmW1s, 0, kt * 32, rank ? w1h : w1g + 1, bar);
    };
  if (wg == 3) {
    asm volatile("barrier.cluster.wait.acquire.aligned;" ::: "memory");
    if (elect()) {
      if (ww < 3) {
        load_stage1(ww + zero, ww);
      } else {
        mbar_expect(BAR(B_XR), 16384);
        bulk_ld(sb + LN_OFF, P.x + cid * 16 * D_ + zero, 16384, BAR(B_XR));
        l2_prefetch(P.w1 + cid * 7168, 14336);
      }
    }
    __syncwarp();
  }
  {
#pragma unroll
    for (int k = 0; k < 7; k++) pr[k] <<= sh16 - 16;
    const float dt = bf_round(__expf(bf_lo(pr[6])));
    const float lr2 = (dt * bf_lo(pr[0])) * 1.4426950408889634f, lit = dt * bf_lo(pr[1]);
    const cf CB = cmul({bf_lo(pr[4]), bf_lo(pr[5])}, {dt * bf_lo(pr[2]), dt * bf_lo(pr[3])});
    if (lr2 != 123.f) TS0(1);
    const uint32_t buf = sb + (wg < 2 ? SSM_OFF : KG_HI - 2 * KG_BUF) + wg * KG_BUF;
    const int m = lane >> 3, r8 = lane & 7;
    const uint32_t bufA = buf + ww * 4096 + m * 1024, bufB = buf + 16384 + ww * 3072;
    const cf z1 = cexp_at(lr2, -lit, 1.f), z8 = cexp_at(lr2, lit, 8.f), z64 = cexp_at(lr2, lit, 64.f), V = cexp_at(lr2, -lit, 256.f);
    const cf z2 = csqr(z1), V2 = csqr(V), V3 = cmul(V2, V);
    cf a0 = CB, a1 = cmul(a0, z64), a2 = cmul(a1, z64), a3 = cmul(a2, z64), p0 = {1.f, 0.f}, p4 = csqr(z2), p1 = V, p2 = csqr(V2);
    const cf q2 = cmul(V2, p4), q3 = cmul(V3, p4);
    stsm4(bufB + 2048 + m * 128 + ((r8 ^ m) << 4), pack2(V2.r, V2.i), pack2(q2.r, q2.i), pack2(V3.r, V3.i), pack2(q3.r, q3.i));
#pragma unroll 1
    for (int t = 0; t < 8; t++) {
      const uint32_t off = t * 128 + ((r8 ^ t) << 4);
      stsm4(bufA + off, pack2(a0.r, a0.i), pack2(a1.r, a1.i), pack2(a2.r, a2.i), pack2(a3.r, a3.i));
      a0 = cmul(a0, z8); a1 = cmul(a1, z8); a2 = cmul(a2, z8); a3 = cmul(a3, z8);
      if (t < 4) {
        stsm4(bufB + m * 512 + (off ^ ((m & 1) << 6)), pack2(p0.r, p0.i), pack2(p4.r, p4.i), pack2(p1.r, p1.i), pack2(p2.r, p2.i));
        p0 = cmul(p0, z1); p4 = cmul(p4, z1); p1 = cmul(p1, z2); p2 = cmul(p2, V);
      }
    }
    ep = ep / NCTA + (sh16 - 15);
    const float k2048 = warp_sum(fmaf(CB.r, p2.r, CB.i * p2.i));
    if (lane == 0) sts32(sb + K2_OFF + warp * 4, __float_as_uint(k2048));
    TS0(2);
    fence_async_smem();
    if (wg != 3) asm volatile("barrier.cluster.wait.acquire.aligned;" ::: "memory");
    if (wg < 2) asm volatile("bar.arrive 2, 512;" ::: "memory");
    TS0(3);
  }

  if (wg >= 2) {
    asm volatile("setmaxnreg.dec.sync.aligned.u32 96;");
    {
    float kacc[24];
    bar_sync(2, 512);
    TS0(4);
    const uint64_t da = mk_desc(sb + SSM_OFF + (wg & 1) * 8192, 16, 1024, 1), db = da + 1024 - (wg & 1) * 128;
    WG_FENCE();
#pragma unroll
    for (int i = 0; i < 16; i++) {
      const int off = (((i < 8 ? 0 : (int)KG_HI - (int)SSM_OFF) + ((i >> 2) & 1) * (int)KG_BUF) >> 4) + 2 * (i & 3);
      wgmma_n48(kacc, da + off, db + off, i != 0);
    }
    WG_COMMIT();
    WG_WAIT(0);
    pin(kacc);
    TS0(5);
    bar_sync(3, 256);
    if (wg == 3) {
      if (warp == 15) {
        uint32_t remote;
        asm volatile("mapa.shared::cluster.u32 %0, %1, %2;" : "=r"(remote) : "r"(BAR(B_KG)), "r"(rank ^ 1));
        if (lane == 0) mbar_arrive_remote_light(remote);
      } else {
        mbar_wait(BAR(B_KG), 0);
        if (elect()) load_stage1(3 + ww, 3 + ww);
        __syncwarp();
      }
    }
    TS(4);
    const int j = 16 * (ww & 1) + g;
    const uint32_t T = sb + KD_OFF + ((wg & 1) * 2 + (ww >> 1)) * KD_CH;
    const uint32_t t1 = c < 2 ? 2 * (256 + 2 * c + 4 * j) : 2 * (384 + 64 * c + j), t1e = c < 2 ? 2 : 64, t1h = c < 2 ? 64 : 16;
#pragma unroll
    for (int hh = 0; hh < 2; hh++) {
      float v[6];
#pragma unroll
      for (int k = 0; k < 6; k++) v[k] = (ww & 2) ? kacc[12 + 4 * (k >> 1) + 2 * hh + (k & 1)] : kacc[4 * (k >> 1) + 2 * hh + (k & 1)];
      sts32(T + 2 * (2 * c + 8 * j) + hh * 128, pack2(v[0], v[1]));
      const uint32_t pk = pack2(v[2], v[3]);
      sts16(T + t1 + hh * t1h, pk); sts16(T + t1 + hh * t1h + t1e, pk >> 16);
      if (c < 2) sts32(T + 2 * (384 + 64 * c + 2 * j) + hh * 32, pack2(v[4], v[5]));
    }
    }
  if (wg == 3) {
    asm volatile("bar.arrive 3, 256;" ::: "memory");
    if (warp == 12) {
#pragma unroll 1
      for (int kt = S1_N; kt < 16; kt++) {
        const int st = kt % S1_N;
        mbar_wait(BAR(B_EMPTY1 + st), kt >= 12);
        if (elect()) load_stage1(kt, st);
        __syncwarp();
      }
      if (KCUT) goto done;
      mbar_wait(BAR(B_EMPTY1 + 3), 0);
      if (elect()) {
        wait_gpu(&g_cnt[C_H + 32 * (rb * 2 + rank)], ep * 4);
        fence_async_global();
        TS(8);
#pragma unroll 1
        for (int it = 0; it < 14; it++) {
          const int s = it & 3;
          if (it >= 4) mbar_wait(BAR(B_EMPTY2 + s), ((it >> 2) - 1) & 1);
          if (it == 2) mbar_wait(BAR(B_HFREE), 0);
          const uint32_t dst = sb + RING_BYTES - S2_BYTES * (s + 1), bar = BAR(B_FULL2 + s);
          mbar_expect(bar, S2_BYTES);
          tma_ld2(dst, &tmHld, rank * 896 + it * 64, rb * 128, bar);
          tma_ld3(dst + 16384, &tmW2, 0, rank * 896 + it * 64, cb * 2 + rank, bar);
          tma_ld3(dst + 24576, &tmW2, 0, rank * 896 + it * 64, cb * 2 + (rank ^ 1), bar);
        }
      }
    } else if (warp == 15) {
#pragma unroll 1
      for (int i = 0; i < 4; i++) sts128(sb + AZ_OFF + i * 512 + lane * 16, 0, 0, 0, 0);
      __syncwarp();
      if (lane == 0) mbar_arrive(BAR(B_LN));
      mbar_wait(BAR(B_LN), 0);
      if (lane == 0) {
#pragma unroll 1
        for (int i = 0; i < 2; i++)
          asm volatile("cp.async.bulk.tensor.2d.global.shared::cta.bulk_group [%0, {%2, %3}], [%1];"
                       ::"l"(&tmXT), "r"(sb + LN_OFF + i * 8192), "r"(cid * 16), "r"(i * 256) : "memory");
        bulk_commit();
        bulk_wait0(); fence_async_global();
        signal_done(&g_cnt[C_LN]);
      }
      __syncwarp();
#pragma unroll
      for (int w = 0; w < 2; w++) sts128(sb + XT_OFF + (2 * w + (lane >> 4)) * XT_CH + (lane & 15) * 16, 0, 0, 0, 0);
      fence_async_smem();
      __syncwarp();
      if (lane == 0) {
        l2_prefetch(P.w2 + cid * 7168, 14336);
        wait_gpu(&g_cnt[C_LN], ep * NCTA);
        fence_async_global();
        mbar_expect(BAR(B_XT), 4 * 4096);
#pragma unroll 1
        for (int w = 0; w < 4; w++) bulk_ld(sb + XT_OFF + w * XT_CH + 256, g_xnT + (cid * 4 + w) * L_, 4096, BAR(B_XT));
      }
      TS(3);
    } else {
      if (KCUT) goto done;
      if (elect()) {
        if (warp == 13) {
          mbar_wait(BAR(B_HST), 0);
#pragma unroll 1
          for (int i = 0; i < 8; i++) {
            tma_st3((i & 3) == 3 ? &tmHh : &tmHs, 0, rb1 * 128 + (i >> 2) * 64, (i & 3) == 3 ? w1h : w1g + (i & 3), sb + i * 8192);
          }
          bulk_commit();
          bulk_wait_read0(); mbar_arrive(BAR(B_HFREE));
          bulk_wait0(); fence_async_global();
          signal_done(&g_cnt[C_H + 32 * (rb1 * 2 + (js >> 2))]);
          TS(7);
        } else {
          mbar_wait(BAR(B_CONV), 0);
          asm volatile("cp.async.bulk.global.shared::cta.bulk_group [%0], [%1], 16384;" ::"l"(g_zT + cid * 4 * L_), "r"(sb + ST_OFF) : "memory");
          bulk_commit();
          uint32_t remote;
          asm volatile("mapa.shared::cluster.u32 %0, %1, %2;" : "=r"(remote) : "r"(BAR(B_PFREE)), "r"(rank ^ 1));
          mbar_arrive_remote_light(remote);
          bulk_wait0(); fence_async_global();
          signal_done(&g_cnt[C_Z]);
          TS(10);
          mbar_expect(BAR(B_EPI), 32768);
          tma_ld2(sb + ST_OFF, &tmXe, oc, rb * 128, BAR(B_EPI));
          wait_gpu(&g_cnt[C_Z], ep * NCTA);
          fence_async_global();
          tma_ld3(sb + ZT_OFF, &tmZ, 0, oc, rb * 2, BAR(B_EPI));
          TS(2);
        }
      }
    }
  } else {
    uint32_t dsk = ldu16(P.dskip + ch);
    if (ww == 1 && elect()) {
      const int cq = cid < 112 ? cid : 0;
      mbar_expect(BAR(B_CW), 16384);
      tma_ld2(sb + CS_OFF, &tmW1c, (cq >> 2) * 64, (cq & 3) * 128, BAR(B_CW));
    }
    {
      const uint32_t T = sb + KD_OFF + ww * KD_CH;
      if (lane == 0) {
        const uint32_t k2 = sb + K2_OFF + ww * 4;
        sts16(T + 2 * 640, pack2((lds<float>(k2) + lds<float>(k2 + 16)) + (lds<float>(k2 + 32) + lds<float>(k2 + 48)), 0.f));
      }
      bar_sync(3, 256);
      const uint32_t E = sb + KC_OFF + ww * KC_CH + lane * 16, O = E + KC_COPY;
      auto P2 = [](uint32_t lo, uint32_t hi) { return __byte_perm(lo, hi, 0x5410); };
#pragma unroll 1
      for (int it = 0; it < 4; it++) {
        const uint32_t ta = T + 2 * (640 - 32 * it - lane);
        const uint32_t a = lds16(ta), b = lds16(ta - 2), t = (lane & 1) ? b : a, aa = P2(a, a), bb = P2(b, b);
        sts128(E + it * 512, aa, aa, P2(t, b), bb); sts128(O + it * 512, aa, P2(a, t), bb, bb);
      }
#pragma unroll 1
      for (int it = 0; it < 2; it++) {
        const uint32_t ta = T + 2 * (512 - 64 * it - 2 * lane);
        const uint32_t a = lds16(ta), b = lds16(ta - 2), cc = lds16(ta - 4), aa = P2(a, a), bb = P2(b, b), c2 = P2(cc, cc);
        sts128(E + 2048 + it * 512, aa, P2(a, b), bb, c2); sts128(O + 2048 + it * 512, aa, bb, P2(b, cc), c2);
      }
      {
        const uint32_t v0 = lds16(T + 2 * (384 - 4 * lane));
        const uint2 q = lds<uint2>(T + 2 * (380 - 4 * lane));
        const uint32_t v22 = __byte_perm(q.y, 0, 0x1010);
        sts128(E + 3072, P2(v0, v0), __byte_perm(q.y, 0, 0x1032), v22, __byte_perm(q.x, 0, 0x1032));
        sts128(O + 3072, __byte_perm(v0, q.y, 0x7610), v22, __byte_perm(q.y, q.x, 0x7610), __byte_perm(q.x, 0, 0x1010));
      }
      {
        const uint32_t v0 = lds16(T + 2 * (256 - 8 * lane));
        uint4 q = lds<uint4>(T + 2 * (248 - 8 * lane));
        asm volatile("" : "+r"(dsk));
        if (lane == 31) q.x = (q.x & 0xffff0000u) | (pack2(bf_lo(q.x) + bf_lo(dsk), 0.f) & 0xffffu);
        sts128(E + 3584, __byte_perm(v0, q.w, 0x7610), __byte_perm(q.w, q.z, 0x7610), __byte_perm(q.z, q.y, 0x7610), __byte_perm(q.y, q.x, 0x7610));
        sts128(O + 3584, __byte_perm(q.w, 0, 0x1032), __byte_perm(q.z, 0, 0x1032), __byte_perm(q.y, 0, 0x1032), __byte_perm(q.x, 0, 0x1032));
        if (lane >= 28) { sts128(E + 4096 - 448 + 16 * ((lane + 1) & 3) - 16 * (lane & 3), lane == 31 ? q.x & 0xffffu : 0u, 0, 0, 0); sts128(O + 4096 - 448, 0, 0, 0, 0); }
      }
      __syncwarp();
      if (lane == 0) mbar_arrive(BAR(B_KRDY + ww));
    }
    TS(29);
    {
      float cs[8];
#pragma unroll
      for (int k = 0; k < 8; k++) cs[k] = 0.f;
      mbar_wait(BAR(B_CW), 0);
#pragma unroll 2
      for (int r = 0; r < 8; r++) {
        const uint4 v = lds<uint4>(sb + CS_OFF + r * 2048 + (tid & 127) * 16);
#pragma unroll
        for (int k = 0; k < 4; k++) { cs[2 * k] += bf_lo((&v.x)[k]); cs[2 * k + 1] += bf_hi((&v.x)[k]); }
      }
#pragma unroll
      for (int k = 0; k < 4; k++) { const bool up = lane & 8; const float snd = up ? cs[k] : cs[k + 4], kp = up ? cs[k + 4] : cs[k]; cs[k] = kp + __shfl_xor_sync(0xffffffffu, snd, 8); }
#pragma unroll
      for (int k = 0; k < 2; k++) { const bool up = lane & 16; const float snd = up ? cs[k] : cs[k + 2], kp = up ? cs[k + 2] : cs[k]; cs[k] = kp + __shfl_xor_sync(0xffffffffu, snd, 16); }
      asm volatile("st.shared.v2.f32 [%0], {%1,%2};" ::"r"(sb + WS_OFF + (tid & 127) * 8), "f"(cs[0]), "f"(cs[1]) : "memory");
    }
    bar_sync(10, 128);
      if (ww == 0) {
        float2 s = make_float2(0.f, 0.f);
#pragma unroll
        for (int k = 0; k < 4; k++) { const float2 v = lds<float2>(sb + WS_OFF + k * 256 + lane * 8); s.x += v.x; s.y += v.y; }
        uint2* p = &g_w1sum[((cid >> 2) * 64 + (lane & 7) * 8 + ((lane >> 3) & 1) * 4 + (lane >> 4) * 2) * 4 + (cid & 3)];
        if (cid < 112) { st_tagged(p, s.x, ep); st_tagged(p + 4, s.y, ep); }
      }
    bar_sync(10, 128);
    TS(17);
    if (KCUT) goto done;
    {
      const int t2 = tid & 127;
      const int c0 = js * 224 + (t2 + 32 * (js & 1)) % 224, c1 = js * 224 + (t2 + 96 + 32 * (js & 1)) % 224;
      const uint32_t b0 = ldu16(P.b1 + c0), b1 = ldu16(P.b1 + c1);
      uint4 r, p0, p1, q0, q1;
#pragma unroll 1
      for (int it = 0;; it++) {
        r = ld_tagged2(&g_stats[rb1 * 128 + t2]);
        p0 = ld_tagged2(&g_w1sum[c0 * 4]); p1 = ld_tagged2(&g_w1sum[c0 * 4 + 2]);
        q0 = ld_tagged2(&g_w1sum[c1 * 4]); q1 = ld_tagged2(&g_w1sum[c1 * 4 + 2]);
        if ((((r.y ^ ep) | (r.w ^ ep) | (p0.y ^ ep)) | ((p0.w ^ ep) | (p1.y ^ ep) | (p1.w ^ ep)) | ((q0.y ^ ep) | (q0.w ^ ep) | (q1.y ^ ep)) | (q1.w ^ ep)) == 0) break;
        if (it > (1 << 20)) __trap();
      }
      mbar_wait(BAR(B_LN), 0);
      const float u = __uint_as_float(r.x), v = __uint_as_float(r.z), uh = bf_round(u), vh = bf_round(v);
      sts128(sb + AX_OFF + t2 * 16, pack2(uh, uh), pack2(u - uh, vh), pack2(v - vh, 0.f), 0);
      sts32(sb + SC_OFF + t2 * 4, __float_as_uint(0.5f * GK * rcp_approx(v)));
      const float s0 = (__uint_as_float(p0.x) + __uint_as_float(p0.z)) + (__uint_as_float(p1.x) + __uint_as_float(p1.z)), h0 = bf_round(s0);
      const float s1 = (__uint_as_float(q0.x) + __uint_as_float(q0.z)) + (__uint_as_float(q1.x) + __uint_as_float(q1.z)), h1 = bf_round(s1);
      sts128(sb + BX_OFF + t2 * 16, pack2(h0, s0 - h0), pack2(h0, bf_lo(b0)), b0, 0);
      sts128(sb + BX_OFF + (t2 + 96) * 16, pack2(h1, s1 - h1), pack2(h1, bf_lo(b1)), b1, 0);
        fence_async_smem();
      __syncwarp();
      if (lane == 0) mbar_arrive(BAR(B_TAB));
    }
    mbar_wait(BAR(B_XT), 0);
    TS(5);
    {
      float acc[8][4];
      conv_mma<true>(acc, sb + KC_OFF + ww * KC_CH, sb + XT_OFF + ww * XT_CH, lane);
#pragma unroll
      for (int j = 0; j < 8; j++) sts128f(sb + CM_OFF + j * 2048 + (tid & 127) * 16, acc[j][0], acc[j][1], acc[j][2], acc[j][3]);
      asm volatile("bar.arrive %0, 64;" ::"r"(5 + ww) : "memory");
    }
    if (lane == 0) mbar_arrive(BAR(B_CONV));
    TS(9);
    {
      const int mi = lane >> 3, r8 = lane & 7;
      uint32_t bb[8];
#pragma unroll
      for (int k = 0; k < 8; k++) bb[k] = __ldg(reinterpret_cast<const uint32_t*>(P.b2 + oc + 8 * k + 2 * c));
      mbar_wait(BAR(B_EPI), 0);
#pragma unroll 1
      for (int h = 0; h < 2; h++) {
#pragma unroll
        for (int q = 0; q < 4; q++) {
          uint32_t xx[4], zz[4];
          ldsm4(xx[0], xx[1], xx[2], xx[3], sb + ST_OFF + (h * 64 + ww * 16 + (lane & 15)) * 128 + (((2 * q + (mi >> 1)) ^ r8) << 4));
          ldsm4t(zz[0], zz[1], zz[2], zz[3], sb + ZT_OFF + h * 8192 + (16 * q + 8 * (mi >> 1) + r8) * 128 + (((2 * ww + (mi & 1)) ^ r8) << 4));
#pragma unroll
          for (int k = 0; k < 4; k++)
            xx[k] = pack2(bf_lo(xx[k]) + bf_lo(zz[k]) + bf_lo(bb[2 * q + (k >> 1)]), bf_hi(xx[k]) + bf_hi(zz[k]) + bf_hi(bb[2 * q + (k >> 1)]));
          sts128(sb + BASE_OFF + q * 4096 + (h * 128 + (tid & 127)) * 16, xx[0], xx[1], xx[2], xx[3]);
        }
      }
      __syncwarp();
      if (lane == 0) mbar_arrive(BAR(B_BASE));
    }
  }
  } else {
    {
      float f[32], s0 = 0.f, s1 = 0.f;
      const int row = tid >> 4;
      uint4 ld[4];
      mbar_wait(BAR(B_XR), 0);
#pragma unroll
      for (int i = 0; i < 4; i++) ld[i] = lds<uint4>(sb + LN_OFF + tid * 16 + row * 768 + i * 256);
#pragma unroll
      for (int k = 0; k < 16; k++) { const uint32_t u = (&ld[k >> 2].x)[k & 3]; f[2 * k] = bf_lo(u); f[2 * k + 1] = bf_hi(u); s0 += f[2 * k]; s1 += f[2 * k + 1]; }
      float mean = (s0 + s1) * (1.f / 32.f), q0 = 0.f, q1 = 0.f;
#pragma unroll
      for (int k = 0; k < 32; k += 2) { const float d0 = f[k] - mean, d1 = f[k + 1] - mean; q0 = fmaf(d0, d0, q0); q1 = fmaf(d1, d1, q1); }
      float m2s = q0 + q1;
#pragma unroll
      for (int o = 1; o < 16; o <<= 1) {
        const float mo = __shfl_xor_sync(0xffffffffu, mean, o), qo = __shfl_xor_sync(0xffffffffu, m2s, o);
        const float dl = mean - mo;
        m2s = fmaf(dl * dl, 16.f * o, m2s + qo);
        mean = 0.5f * (mean + mo);
      }
      const float var = m2s * (1.f / D_);
      const float mb = bf_round(mean), sd1 = bf_round(sqrt_approx(bf_round(bf_round(var) + 1e-5f))), rs1 = rcp_approx(sd1);
      const float m2b = bf_round((mean - mb) * rs1), sd2 = bf_round(sqrt_approx(bf_round(bf_round(var * rs1 * rs1) + 1e-5f)));
      const float sh = -mb * rs1;
      const uint32_t ra = sb + LN_OFF + row * 1024 + (((tid & 15) ^ (((row >> 2) << 1) | (row & 1))) << 4);
#pragma unroll
      for (int i = 0; i < 4; i++)
        sts128(ra + 256 * i, pack2(fmaf(f[8 * i], rs1, sh), fmaf(f[8 * i + 1], rs1, sh)), pack2(fmaf(f[8 * i + 2], rs1, sh), fmaf(f[8 * i + 3], rs1, sh)),
               pack2(fmaf(f[8 * i + 4], rs1, sh), fmaf(f[8 * i + 5], rs1, sh)), pack2(fmaf(f[8 * i + 6], rs1, sh), fmaf(f[8 * i + 7], rs1, sh)));
      TS0(4);
      bar_sync(1, 256);
      TS0(5);
      const int m = lane >> 3, rho = lane & 7;
      const uint32_t la = sb + LN_OFF + (4 * (rho >> 1) + (rho & 1) + 2 * (m & 1)) * 1024 + warp * 128;
      uint32_t r[4][4];
#pragma unroll
      for (int i = 0; i < 4; i++) ldsm4t(r[i][0], r[i][1], r[i][2], r[i][3], la + (((2 * i + (m >> 1)) ^ rho) << 4));
      bar_sync(1, 256);
      const uint32_t ta = sb + LN_OFF + (warp * 64 + g) * 32 + ((((lane >> 1) ^ (cid >> 2)) & 1) << 4) + ((lane & 1) << 3);
#pragma unroll
      for (int i = 0; i < 8; i++)
        asm volatile("st.shared.v2.u32 [%0], {%1,%2};" ::"r"(ta + i * 256), "r"(r[i >> 1][2 * (i & 1)]), "r"(r[i >> 1][2 * (i & 1) + 1]) : "memory");
      fence_async_smem();
      __syncwarp();
      if (lane == 0) mbar_arrive(BAR(B_LN));
      if ((lane & 14) == 0)
        st_tagged(reinterpret_cast<uint2*>(&g_stats[cid * 16 + (tid >> 4)]) + (lane & 1), (lane & 1) ? sd1 * sd2 : -fmaf(m2b, sd1, mb), ep);
      TS0(6);
    }
    asm volatile("setmaxnreg.inc.sync.aligned.u32 160;");
    TS0(7);
    uint32_t rsb;
    asm volatile("mapa.shared::cluster.u32 %0, %1, %2;" : "=r"(rsb) : "r"(sb), "r"(rank ^ 1));
    {
      float accA[64], accB[48];
      int st = 0, prev = 0;
#pragma unroll 1
      for (int kt = 0; kt < 16; kt++) {
        mbar_wait(BAR(B_FULL1 + st), kt >= 6 && kt < 12);
        if (kt == 0) TS(18);
        if (kt == 6) TS(19);
        const uint64_t da = mk_desc(sb + st * S1_BYTES + wg * 4096, 16, 512, 2);
        const uint64_t db = mk_desc(sb + st * S1_BYTES + 8192, 4096, 1024, 1);
        WG_FENCE();
#pragma unroll
        for (int kk = 0; kk < 2; kk++) {
          wgmma_n128_tb(accA, da + 2 * kk, db + 128 * kk, (kt | kk) != 0);
          wgmma_n96_tb(accB, da + 2 * kk, db + 512 + 128 * kk, (kt | kk) != 0);
        }
        WG_COMMIT();
        WG_WAIT(1);
        if (kt > 0 && lane == 0) { mbar_arrive(BAR(B_EMPTY1 + prev)); mbar_arrive_remote_light(rsb + BAR_OFF + 8 * (B_EMPTY1 + prev)); }
        prev = st;
        st = st == S1_N - 1 ? 0 : st + 1;
      }
      TS(11);
      if (KCUT) { WG_WAIT(0); pin(accA); pin(accB); if (accA[0] + accB[3] == 1.234f) sts32(sb, 1); goto done; }
      mbar_wait(BAR(B_TAB), 0);
      TS(23);
      {
        const uint64_t da = mk_desc(sb + AZ_OFF + wg * 1024, 2048, 128, 0), db = mk_desc(sb + BX_OFF, 0, 128, 0);
        WG_FENCE();
        wgmma_n128(accA, da, db, 1);
        wgmma_n96(accB, da, db + 128, 1);
        WG_COMMIT();
      }
      WG_WAIT(0);
      pin(accA); pin(accB);
      if (lane == 0) { mbar_arrive(BAR(B_EMPTY1 + 3)); mbar_arrive_remote_light(rsb + BAR_OFF + 8 * (B_EMPTY1 + 3)); }
      TS(31);
      bar_sync(1, 256);
      const uint32_t hw = sb + wg * 32768 + ww * 2048;
      {
        const uint32_t hrow = hw + (lane & 15) * 128;
        const float s0 = lds<float>(sb + SC_OFF + (wg * 64 + ww * 16 + g) * 4), s1 = lds<float>(sb + SC_OFF + (wg * 64 + ww * 16 + g + 8) * 4);
#pragma unroll
        for (int t = 0; t < 28; t += 2) {
          const float* a = t < 16 ? &accA[4 * t] : &accB[4 * (t - 16)];
          stsm4(hrow + (t >> 3) * 8192 + ((((t & 7) + (lane >> 4)) ^ (lane & 7)) << 4),
                gelu2(a[0] * s0, a[1] * s0), gelu2(a[2] * s1, a[3] * s1), gelu2(a[4] * s0, a[5] * s0), gelu2(a[6] * s1, a[7] * s1));
        }
      }
      fence_async_smem();
      __syncwarp();
      if (lane == 0) mbar_arrive(BAR(B_HST));
      TS(6);
    }
    mbar_wait(BAR(B_KRDY + ww), 0);
    mbar_wait(BAR(B_XT), 0);
    TS(24);
    {
      float acc[8][4];
      conv_mma<false>(acc, sb + KC_OFF + ww * KC_CH, sb + XT_OFF + ww * XT_CH + wg * 2048, lane);
      if (wg == 1) {
        bar_sync(5 + ww, 64);
#pragma unroll
        for (int j = 0; j < 8; j++) {
          const float4 o = lds<float4>(sb + CM_OFF + j * 2048 + (tid & 127) * 16);
          acc[j][0] += o.x; acc[j][1] += o.y; acc[j][2] += o.z; acc[j][3] += o.w;
        }
      }
      mbar_wait(BAR(B_HFREE), 0);
      const uint32_t za = sb + ST_OFF + ww * 4096 + wg * 2048 + (lane >> 4) * 256 + (lane & 7) * 32 + (lane & 8) * 2;
#pragma unroll
      for (int j = 0; j < 8; j += 2)
        asm volatile("stmatrix.sync.aligned.m8n8.x4.trans.shared.b16 [%0], {%1,%2,%3,%4};" ::"r"(za + j * 256), "r"(pack2(acc[j][0], acc[j][1])),
                     "r"(pack2(acc[j][2], acc[j][3])), "r"(pack2(acc[j + 1][0], acc[j + 1][1])), "r"(pack2(acc[j + 1][2], acc[j + 1][3])) : "memory");
      fence_async_smem();
    }
    __syncwarp();
    if (lane == 0) mbar_arrive(BAR(B_CONV));
    TS(12);
    mbar_wait(BAR(B_CONV), 0);
    float acc[64];
#pragma unroll 1
    for (int it = 0; it < 14; it++) {
      const int s = it & 3;
      mbar_wait(BAR(B_FULL2 + s), (it >> 2) & 1);
      if (it == 0) TS(25);
      if (it == 4) TS(26);
      const uint32_t base = sb + RING_BYTES - S2_BYTES * (s + 1);
      const uint64_t da = mk_desc(base + wg * 8192, 16, 1024, 1), db = mk_desc(base + 16384, 8192, 1024, 1);
      WG_FENCE();
#pragma unroll
      for (int kk = 0; kk < 4; kk++) wgmma_n128_tb(acc, da + 2 * kk, db + 128 * kk, (it | kk) != 0);
      WG_COMMIT();
      WG_WAIT(1);
      if (it > 0 && lane == 0) mbar_arrive(BAR(B_EMPTY2 + ((it - 1) & 3)));
    }
    WG_WAIT(0);
    pin(acc);
    TS(13);
    mbar_wait_cluster(BAR(B_PFREE), 0);
#pragma unroll
    for (int i = 0; i < 8; i++)
      asm volatile("st.async.weak.shared::cluster.mbarrier::complete_tx::bytes.v4.f32 [%0], {%1,%2,%3,%4}, [%5];"
                   ::"r"(rsb + RED_OFF + tid * 16 + i * 4096), "f"(acc[32 + 4 * i]), "f"(acc[33 + 4 * i]), "f"(acc[34 + 4 * i]),
                     "f"(acc[35 + 4 * i]), "r"(rsb + BAR_OFF + 8 * B_RED) : "memory");
    mbar_wait(BAR(B_BASE), 0);
#pragma unroll
    for (int q = 0; q < 4; q++) {
      const uint4 p = lds<uint4>(sb + BASE_OFF + q * 4096 + tid * 16);
#pragma unroll
      for (int k = 0; k < 4; k++) {
        acc[8 * q + 2 * k] = fmaf(acc[8 * q + 2 * k], 1.f / GK, bf_lo((&p.x)[k]));
        acc[8 * q + 2 * k + 1] = fmaf(acc[8 * q + 2 * k + 1], 1.f / GK, bf_hi((&p.x)[k]));
      }
    }
    mbar_wait_cluster(BAR(B_RED), 0);
    TS(27);
#pragma unroll
    for (int q = 0; q < 4; q++) {
      const float4 p0 = lds<float4>(sb + RED_OFF + 2 * q * 4096 + tid * 16), p1 = lds<float4>(sb + RED_OFF + (2 * q + 1) * 4096 + tid * 16);
      stsm4(sb + ST_OFF + (wg * 64 + ww * 16 + (lane & 15)) * 128 + (((2 * q + (lane >> 4)) ^ (lane & 7)) << 4),
            pack2(fmaf(p0.x, 1.f / GK, acc[8 * q]), fmaf(p0.y, 1.f / GK, acc[8 * q + 1])), pack2(fmaf(p0.z, 1.f / GK, acc[8 * q + 2]), fmaf(p0.w, 1.f / GK, acc[8 * q + 3])),
            pack2(fmaf(p1.x, 1.f / GK, acc[8 * q + 4]), fmaf(p1.y, 1.f / GK, acc[8 * q + 5])), pack2(fmaf(p1.z, 1.f / GK, acc[8 * q + 6]), fmaf(p1.w, 1.f / GK, acc[8 * q + 7])));
    }
    fence_async_smem();
    __syncwarp();
    if (elect()) {
      asm volatile("cp.async.bulk.tensor.2d.global.shared::cta.bulk_group [%0, {%2, %3}], [%1];"
                   ::"l"(&tmOut), "r"(sb + ST_OFF + warp * 2048), "r"(oc), "r"(rb * 128 + warp * 16) : "memory");
      bulk_commit();
      bulk_wait_read0();
    }
    TS(14);
  }
done:
  if (KCUT) { mbar_wait(BAR(B_XT), 0); __syncwarp(); asm volatile("barrier.cluster.arrive.aligned;\nbarrier.cluster.wait.aligned;" ::: "memory"); }
  TS_DUMP();
}

typedef CUresult (*EncodeFn)(CUtensorMap*, CUtensorMapDataType, cuuint32_t, void*, const cuuint64_t*, const cuuint64_t*,
                             const cuuint32_t*, const cuuint32_t*, CUtensorMapInterleave, CUtensorMapSwizzle,
                             CUtensorMapL2promotion, CUtensorMapFloatOOBfill);

CUtensorMap make_map(EncodeFn enc, const void* ptr, int rank, const cuuint64_t* dims, const cuuint64_t* strides,
                     const cuuint32_t* box, CUtensorMapSwizzle swz) {
  CUtensorMap m;
  const cuuint32_t es[3] = {1, 1, 1};
  enc(&m, CU_TENSOR_MAP_DATA_TYPE_BFLOAT16, rank, const_cast<void*>(ptr), dims, strides, box, es, CU_TENSOR_MAP_INTERLEAVE_NONE,
      swz, CU_TENSOR_MAP_L2_PROMOTION_L2_128B, CU_TENSOR_MAP_FLOAT_OOB_FILL_NONE);
  return m;
}

}

extern "C" void kernel_launch(void* const* d_in, const int* in_sizes, int n_in, void* d_out, int out_size) {
  (void)in_sizes; (void)n_in; (void)out_size;
  typedef const __nv_bfloat16* bp;
  Params P = {(bp)d_in[0], (bp)d_in[1], (bp)d_in[2], (bp)d_in[3], (bp)d_in[4], (bp)d_in[5], (bp)d_in[6], (bp)d_in[7],
              (bp)d_in[8], (bp)d_in[10], (bp)d_in[11], (bp)d_in[12], (bp)d_in[13]};
  void* fn = nullptr;
  cudaDriverEntryPointQueryResult qr;
  cudaGetDriverEntryPoint("cuTensorMapEncodeTiled", &fn, cudaEnableDefault, &qr);
  EncodeFn enc = (EncodeFn)fn;
  void *ph, *pz;
  cudaGetSymbolAddress(&ph, g_h);
  cudaGetSymbolAddress(&pz, g_zT);
  const cuuint64_t dX[2] = {D_, L_}, sX[1] = {D_ * 2};
  const cuuint32_t bX1[2] = {32, 128}, bXe[2] = {64, 128}, bW1[3] = {64, 32, 1}, b64[3] = {64, 64, 1}, bZ[3] = {64, 64, 2}, bOut[2] = {64, 16};
  const cuuint64_t dW1[3] = {64, D_, F_ / 64}, dW1h[3] = {32, D_, F_ / 32}, sF[2] = {F_ * 2, 128}, sFh[2] = {F_ * 2, 64};
  const cuuint64_t dHs[3] = {64, L_, F_ / 64}, dHh[3] = {32, L_, F_ / 32}, dHl[2] = {F_, L_};
  const cuuint64_t dW2[3] = {64, F_, D_ / 64}, sW2[2] = {D_ * 2, 128}, dZ[3] = {64, D_, L_ / 64}, sZ[2] = {L_ * 2, 128};
  CUtensorMap tmX1 = make_map(enc, P.x, 2, dX, sX, bX1, CU_TENSOR_MAP_SWIZZLE_64B);
  CUtensorMap tmW1s = make_map(enc, P.w1, 3, dW1, sF, bW1, CU_TENSOR_MAP_SWIZZLE_128B);
  CUtensorMap tmW1h = make_map(enc, P.w1, 3, dW1h, sFh, bW1, CU_TENSOR_MAP_SWIZZLE_128B);
  CUtensorMap tmHs = make_map(enc, ph, 3, dHs, sF, b64, CU_TENSOR_MAP_SWIZZLE_128B);
  CUtensorMap tmHh = make_map(enc, ph, 3, dHh, sFh, b64, CU_TENSOR_MAP_SWIZZLE_128B);
  CUtensorMap tmHld = make_map(enc, ph, 2, dHl, sF, bXe, CU_TENSOR_MAP_SWIZZLE_128B);
  CUtensorMap tmW2 = make_map(enc, P.w2, 3, dW2, sW2, b64, CU_TENSOR_MAP_SWIZZLE_128B);
  CUtensorMap tmXe = make_map(enc, P.x, 2, dX, sX, bXe, CU_TENSOR_MAP_SWIZZLE_128B);
  CUtensorMap tmZ = make_map(enc, pz, 3, dZ, sZ, bZ, CU_TENSOR_MAP_SWIZZLE_128B);
  const cuuint64_t dW1c[2] = {F_, D_}, dXT[2] = {L_, D_};
  const cuuint32_t bXT[2] = {16, 256};
  void* pxt;
  cudaGetSymbolAddress(&pxt, g_xnT);
  CUtensorMap tmW1c = make_map(enc, P.w1, 2, dW1c, sF, bXe, CU_TENSOR_MAP_SWIZZLE_NONE);
  CUtensorMap tmXT = make_map(enc, pxt, 2, dXT, sZ, bXT, CU_TENSOR_MAP_SWIZZLE_NONE);
  CUtensorMap tmOut = make_map(enc, d_out, 2, dX, sX, bOut, CU_TENSOR_MAP_SWIZZLE_128B);
  cudaFuncSetAttribute(fused_kernel, cudaFuncAttributeMaxDynamicSharedMemorySize, SMEM_BYTES);
  fused_kernel<<<NCTA, 512, SMEM_BYTES, cudaStreamPerThread>>>(tmX1, tmW1s, tmW1h, tmHs, tmHh, tmHld, tmW2, tmXe, tmZ, tmOut, tmW1c, tmXT, P);
}
```

```cpp
#include <cuda_runtime.h>
#include <cuda_bf16.h>
#include <cuda.h>
#include <stdint.h>

extern __shared__ __align__(1024) uint8_t smem_raw[];

namespace {

constexpr int L_ = 2048, D_ = 512, F_ = 1792, NM_ = 128;
constexpr int NCTA = 128;

constexpr uint32_t S1_BYTES = 24576, S1_N = 6;
constexpr uint32_t RING_BYTES = S1_BYTES * S1_N;
constexpr uint32_t S2_BYTES = 32768;
constexpr uint32_t XT_OFF = RING_BYTES;
constexpr uint32_t XT_CH = 4352;
constexpr uint32_t LN_OFF = XT_OFF;
constexpr uint32_t AZ_OFF = XT_OFF + 4 * XT_CH;
constexpr uint32_t AX_OFF = AZ_OFF + 2048;
constexpr uint32_t BX_OFF = AX_OFF + 2048;
constexpr uint32_t SC_OFF = BX_OFF + 3584;
constexpr uint32_t SSM_OFF = SC_OFF + 512;
constexpr uint32_t KG_BUF = 28672;
constexpr uint32_t KG_HI = RING_BYTES - 2 * KG_BUF;
constexpr uint32_t KN_COPY = 1088, KA_OFF = 2 * KN_COPY, KA_COPY = 192, KB_OFF = KA_OFF + 4 * KA_COPY, KB_COPY = 320;
constexpr uint32_t TAP_CH = KB_OFF + 4 * KB_COPY;
constexpr uint32_t UA_LEN = 3088, UB_LEN = 2064, U_CH = 2 * UA_LEN + 2 * UB_LEN;
constexpr uint32_t U_OFF = SSM_OFF + 4 * TAP_CH;
constexpr uint32_t KD_OFF = U_OFF;
constexpr uint32_t KD_CH = 1312;
constexpr uint32_t TR_OFF = U_OFF + 8192;
constexpr uint32_t RED_OFF = XT_OFF;
constexpr uint32_t BASE_OFF = RED_OFF + 16384;
constexpr uint32_t ZT_OFF = BASE_OFF + 16384;
constexpr uint32_t ST_OFF = 0;
constexpr uint32_t K2_OFF = U_OFF + 4 * U_CH;
constexpr uint32_t BAR_OFF = K2_OFF + 128;
constexpr uint32_t WS_OFF = XT_OFF + 16384;
constexpr uint32_t EPOCH_OFF = BAR_OFF + 384;
constexpr uint32_t SMEM_BYTES = EPOCH_OFF + 16 + 128 + 512;
static_assert(2 * KG_BUF <= K2_OFF - SSM_OFF && ((SSM_OFF | AZ_OFF | ZT_OFF) & 1023) == 0 && (KD_OFF & 15) == 0, "smem");
static_assert(SMEM_BYTES <= 232448, "smem");

enum { B_FULL1 = 0, B_EMPTY1 = 6, B_FULL2 = 12, B_EMPTY2 = 16, B_HST = 20  , B_BASE = 22, B_KG = 26, B_LN = 24, B_CONV = 25,
       B_TAB = 23, B_HFREE = 27, B_KRDY = 28, B_XT = 32, B_PFREE = 33, B_EPI = 34, B_RED = 35, B_XR = 36, B_G1 = 37 };

__device__ __align__(1024) __nv_bfloat16 g_h[L_ * F_];
__device__ __align__(1024) __nv_bfloat16 g_xnT[D_ * L_];
__device__ __align__(1024) __nv_bfloat16 g_zT[D_ * L_];
__device__ __align__(256) uint4 g_stats[L_];
__device__ __align__(256) uint2 g_w1sum[F_ * 4];
__device__ __align__(256) unsigned g_cnt[64 * 32];
enum { C_LN = 32, C_Z = 64, C_H = 96   };

__device__ __forceinline__ uint32_t smem_u32(const void* p) { return (uint32_t)__cvta_generic_to_shared(p); }
__device__ __forceinline__ void mbar_init(uint32_t bar, uint32_t cnt) {
  asm volatile("mbarrier.init.shared::cta.b64 [%0], %1;" ::"r"(bar), "r"(cnt) : "memory");
}
__device__ __forceinline__ void mbar_arrive(uint32_t bar) {
  asm volatile("mbarrier.arrive.shared::cta.b64 _, [%0];" ::"r"(bar) : "memory");
}
__device__ __forceinline__ void mbar_arrive_remote_light(uint32_t bar_cluster) {
  asm volatile("mbarrier.arrive.shared::cluster.b64 _, [%0];" ::"r"(bar_cluster) : "memory");
}
__device__ __forceinline__ void mbar_expect(uint32_t bar, uint32_t bytes) {
  asm volatile("mbarrier.arrive.expect_tx.shared::cta.b64 _, [%0], %1;" ::"r"(bar), "r"(bytes) : "memory");
}
#define MBAR_WAIT_BODY(SEM)                                                                                      \
  asm volatile("{\n.reg .pred p;\nW:\nmbarrier.try_wait.parity" SEM ".shared::cta.b64 p, [%0], %1, 1000000;\n@!p bra W;\n}" \
               ::"r"(bar), "r"(parity) : "memory");
__device__ __forceinline__ void mbar_wait(uint32_t bar, uint32_t parity) { MBAR_WAIT_BODY("") }
__device__ __forceinline__ void mbar_wait_cluster(uint32_t bar, uint32_t parity) { MBAR_WAIT_BODY(".acquire.cluster") }
__device__ __forceinline__ bool elect() {
  uint32_t p;
  asm volatile("{\n.reg .pred p;\nelect.sync _|p, 0xffffffff;\nselp.u32 %0, 1, 0, p;\n}" : "=r"(p));
  return p != 0;
}
__device__ __forceinline__ void bar_sync(int id, int n) { asm volatile("bar.sync %0, %1;" ::"r"(id), "r"(n) : "memory"); }
__device__ __forceinline__ void fence_async_smem() { asm volatile("fence.proxy.async.shared::cta;" ::: "memory"); }
__device__ __forceinline__ void fence_async_global() { asm volatile("fence.proxy.async.global;" ::: "memory"); }
__device__ __forceinline__ void tma_ld2(uint32_t dst, const CUtensorMap* m, int c0, int c1, uint32_t bar) {
  asm volatile("cp.async.bulk.tensor.2d.shared::cluster.global.mbarrier::complete_tx::bytes [%0], [%1, {%3, %4}], [%2];"
               ::"r"(dst), "l"(m), "r"(bar), "r"(c0), "r"(c1) : "memory");
}
__device__ __forceinline__ void tma_ld3(uint32_t dst, const CUtensorMap* m, int c0, int c1, int c2, uint32_t bar) {
  asm volatile("cp.async.bulk.tensor.3d.shared::cluster.global.mbarrier::complete_tx::bytes [%0], [%1, {%3, %4, %5}], [%2];"
               ::"r"(dst), "l"(m), "r"(bar), "r"(c0), "r"(c1), "r"(c2) : "memory");
}
__device__ __forceinline__ void tma_ld3_mc(uint32_t dst, const CUtensorMap* m, int c0, int c1, int c2, uint32_t bar) {
  asm volatile("cp.async.bulk.tensor.3d.shared::cluster.global.mbarrier::complete_tx::bytes.multicast::cluster [%0], [%1, {%3, %4, %5}], [%2], %6;"
               ::"r"(dst), "l"(m), "r"(bar), "r"(c0), "r"(c1), "r"(c2), "h"((uint16_t)3) : "memory");
}
__device__ __forceinline__ void tma_st3(const CUtensorMap* m, int c0, int c1, int c2, uint32_t src) {
  asm volatile("cp.async.bulk.tensor.3d.global.shared::cta.bulk_group [%0, {%2, %3, %4}], [%1];"
               ::"l"(m), "r"(src), "r"(c0), "r"(c1), "r"(c2) : "memory");
}
__device__ __forceinline__ void bulk_ld(uint32_t dst, const void* src, uint32_t bytes, uint32_t bar) {
  asm volatile("cp.async.bulk.shared::cluster.global.mbarrier::complete_tx::bytes [%0], [%1], %2, [%3];"
               ::"r"(dst), "l"(src), "r"(bytes), "r"(bar) : "memory");
}
__device__ __forceinline__ void bulk_commit() { asm volatile("cp.async.bulk.commit_group;" ::: "memory"); }
__device__ __forceinline__ void bulk_wait_read0() { asm volatile("cp.async.bulk.wait_group.read 0;" ::: "memory"); }
__device__ __forceinline__ void bulk_wait0() { asm volatile("cp.async.bulk.wait_group 0;" ::: "memory"); }
__device__ __forceinline__ void prefetch_map(const CUtensorMap* m) { asm volatile("prefetch.tensormap [%0];" ::"l"(m) : "memory"); }
__device__ __forceinline__ void l2_prefetch(const void* p, uint32_t bytes) {
  asm volatile("cp.async.bulk.prefetch.L2.global [%0], %1;" ::"l"(p), "r"(bytes) : "memory");
}
__device__ __forceinline__ void signal_done(unsigned* p) { asm volatile("red.relaxed.gpu.global.add.u32 [%0], 1;" ::"l"(p) : "memory"); }
__device__ __forceinline__ void st_tagged(void* p, float v, uint32_t tag) {
  asm volatile("st.relaxed.gpu.global.b64 [%0], %1;" ::"l"(p), "l"((uint64_t)__float_as_uint(v) | ((uint64_t)tag << 32)) : "memory");
}
__device__ __forceinline__ uint4 ld_tagged2(const void* p) {
  uint64_t a, b;
  asm volatile("ld.relaxed.gpu.global.v2.b64 {%0,%1}, [%2];" : "=l"(a), "=l"(b) : "l"(p) : "memory");
  return make_uint4((uint32_t)a, (uint32_t)(a >> 32), (uint32_t)b, (uint32_t)(b >> 32));
}
__device__ __forceinline__ void wait_gpu(const unsigned* p, unsigned target) {
#pragma unroll 1
  for (int it = 0; it < (1 << 22); it++) {
    unsigned v;
    asm volatile("ld.relaxed.gpu.global.u32 %0, [%1];" : "=r"(v) : "l"(p) : "memory");
    if ((int)(v - target) >= 0) return;
    __nanosleep(20);
  }
  __trap();
}
__device__ __forceinline__ uint64_t mk_desc(uint32_t addr, uint32_t lbo, uint32_t sbo, uint32_t swz) {
  return (uint64_t)((addr & 0x3FFFF) >> 4) | ((uint64_t)(lbo >> 4) << 16) | ((uint64_t)(sbo >> 4) << 32) | ((uint64_t)swz << 62);
}
#define WG_FENCE() asm volatile("wgmma.fence.sync.aligned;" ::: "memory")
#define WG_COMMIT() asm volatile("wgmma.commit_group.sync.aligned;" ::: "memory")
#define WG_WAIT(n) asm volatile("wgmma.wait_group.sync.aligned %0;" ::"n"(n) : "memory")
template <int N> __device__ __forceinline__ void pin(float (&d)[N]) {
#pragma unroll
  for (int i = 0; i < N; i++) asm volatile("" : "+f"(d[i])::"memory");
}
__device__ __forceinline__ void wgmma_n96_tb(float (&d)[48], uint64_t da, uint64_t db, int scale_d) {
  asm volatile("{\n.reg .pred p;\nsetp.ne.b32 p, %50, 0;\n"
    "wgmma.mma_async.sync.aligned.m64n96k16.f32.bf16.bf16 {%0, %1, %2, %3, %4, %5, %6, %7, %8, %9, %10, %11, %12, %13, %14, %15, %16, %17, %18, %19, %20, %21, %22, %23, %24, %25, %26, %27, %28, %29, %30, %31, %32, %33, %34, %35, %36, %37, %38, %39, %40, %41, %42, %43, %44, %45, %46, %47}, %48, %49, p, 1, 1, 0, 1;\n}"
   : "+f"(d[0]), "+f"(d[1]), "+f"(d[2]), "+f"(d[3]), "+f"(d[4]), "+f"(d[5]), "+f"(d[6]), "+f"(d[7]), "+f"(d[8]), "+f"(d[9]), "+f"(d[10]), "+f"(d[11]), "+f"(d[12]), "+f"(d[13]), "+f"(d[14]), "+f"(d[15]), "+f"(d[16]), "+f"(d[17]), "+f"(d[18]), "+f"(d[19]), "+f"(d[20]), "+f"(d[21]), "+f"(d[22]), "+f"(d[23]), "+f"(d[24]), "+f"(d[25]), "+f"(d[26]), "+f"(d[27]), "+f"(d[28]), "+f"(d[29]), "+f"(d[30]), "+f"(d[31]), "+f"(d[32]), "+f"(d[33]), "+f"(d[34]), "+f"(d[35]), "+f"(d[36]), "+f"(d[37]), "+f"(d[38]), "+f"(d[39]), "+f"(d[40]), "+f"(d[41]), "+f"(d[42]), "+f"(d[43]), "+f"(d[44]), "+f"(d[45]), "+f"(d[46]), "+f"(d[47])
   : "l"(da), "l"(db), "r"(scale_d));
}
__device__ __forceinline__ void wgmma_n128_tb(float (&d)[64], uint64_t da, uint64_t db, int scale_d) {
  asm volatile("{\n.reg .pred p;\nsetp.ne.b32 p, %66, 0;\n"
    "wgmma.mma_async.sync.aligned.m64n128k16.f32.bf16.bf16 {%0, %1, %2, %3, %4, %5, %6, %7, %8, %9, %10, %11, %12, %13, %14, %15, %16, %17, %18, %19, %20, %21, %22, %23, %24, %25, %26, %27, %28, %29, %30, %31, %32, %33, %34, %35, %36, %37, %38, %39, %40, %41, %42, %43, %44, %45, %46, %47, %48, %49, %50, %51, %52, %53, %54, %55, %56, %57, %58, %59, %60, %61, %62, %63}, %64, %65, p, 1, 1, 0, 1;\n}"
   : "+f"(d[0]), "+f"(d[1]), "+f"(d[2]), "+f"(d[3]), "+f"(d[4]), "+f"(d[5]), "+f"(d[6]), "+f"(d[7]), "+f"(d[8]), "+f"(d[9]), "+f"(d[10]), "+f"(d[11]), "+f"(d[12]), "+f"(d[13]), "+f"(d[14]), "+f"(d[15]), "+f"(d[16]), "+f"(d[17]), "+f"(d[18]), "+f"(d[19]), "+f"(d[20]), "+f"(d[21]), "+f"(d[22]), "+f"(d[23]), "+f"(d[24]), "+f"(d[25]), "+f"(d[26]), "+f"(d[27]), "+f"(d[28]), "+f"(d[29]), "+f"(d[30]), "+f"(d[31]), "+f"(d[32]), "+f"(d[33]), "+f"(d[34]), "+f"(d[35]), "+f"(d[36]), "+f"(d[37]), "+f"(d[38]), "+f"(d[39]), "+f"(d[40]), "+f"(d[41]), "+f"(d[42]), "+f"(d[43]), "+f"(d[44]), "+f"(d[45]), "+f"(d[46]), "+f"(d[47]), "+f"(d[48]), "+f"(d[49]), "+f"(d[50]), "+f"(d[51]), "+f"(d[52]), "+f"(d[53]), "+f"(d[54]), "+f"(d[55]), "+f"(d[56]), "+f"(d[57]), "+f"(d[58]), "+f"(d[59]), "+f"(d[60]), "+f"(d[61]), "+f"(d[62]), "+f"(d[63])
   : "l"(da), "l"(db), "r"(scale_d));
}
__device__ __forceinline__ void wgmma_n96(float (&d)[48], uint64_t da, uint64_t db, int scale_d) {
  asm volatile("{\n.reg .pred p;\nsetp.ne.b32 p, %50, 0;\n"
    "wgmma.mma_async.sync.aligned.m64n96k16.f32.bf16.bf16 {%0, %1, %2, %3, %4, %5, %6, %7, %8, %9, %10, %11, %12, %13, %14, %15, %16, %17, %18, %19, %20, %21, %22, %23, %24, %25, %26, %27, %28, %29, %30, %31, %32, %33, %34, %35, %36, %37, %38, %39, %40, %41, %42, %43, %44, %45, %46, %47}, %48, %49, p, 1, 1, 0, 0;\n}"
   : "+f"(d[0]), "+f"(d[1]), "+f"(d[2]), "+f"(d[3]), "+f"(d[4]), "+f"(d[5]), "+f"(d[6]), "+f"(d[7]), "+f"(d[8]), "+f"(d[9]), "+f"(d[10]), "+f"(d[11]), "+f"(d[12]), "+f"(d[13]), "+f"(d[14]), "+f"(d[15]), "+f"(d[16]), "+f"(d[17]), "+f"(d[18]), "+f"(d[19]), "+f"(d[20]), "+f"(d[21]), "+f"(d[22]), "+f"(d[23]), "+f"(d[24]), "+f"(d[25]), "+f"(d[26]), "+f"(d[27]), "+f"(d[28]), "+f"(d[29]), "+f"(d[30]), "+f"(d[31]), "+f"(d[32]), "+f"(d[33]), "+f"(d[34]), "+f"(d[35]), "+f"(d[36]), "+f"(d[37]), "+f"(d[38]), "+f"(d[39]), "+f"(d[40]), "+f"(d[41]), "+f"(d[42]), "+f"(d[43]), "+f"(d[44]), "+f"(d[45]), "+f"(d[46]), "+f"(d[47])
   : "l"(da), "l"(db), "r"(scale_d));
}
__device__ __forceinline__ void wgmma_n128(float (&d)[64], uint64_t da, uint64_t db, int scale_d) {
  asm volatile("{\n.reg .pred p;\nsetp.ne.b32 p, %66, 0;\n"
    "wgmma.mma_async.sync.aligned.m64n128k16.f32.bf16.bf16 {%0, %1, %2, %3, %4, %5, %6, %7, %8, %9, %10, %11, %12, %13, %14, %15, %16, %17, %18, %19, %20, %21, %22, %23, %24, %25, %26, %27, %28, %29, %30, %31, %32, %33, %34, %35, %36, %37, %38, %39, %40, %41, %42, %43, %44, %45, %46, %47, %48, %49, %50, %51, %52, %53, %54, %55, %56, %57, %58, %59, %60, %61, %62, %63}, %64, %65, p, 1, 1, 0, 0;\n}"
   : "+f"(d[0]), "+f"(d[1]), "+f"(d[2]), "+f"(d[3]), "+f"(d[4]), "+f"(d[5]), "+f"(d[6]), "+f"(d[7]), "+f"(d[8]), "+f"(d[9]), "+f"(d[10]), "+f"(d[11]), "+f"(d[12]), "+f"(d[13]), "+f"(d[14]), "+f"(d[15]), "+f"(d[16]), "+f"(d[17]), "+f"(d[18]), "+f"(d[19]), "+f"(d[20]), "+f"(d[21]), "+f"(d[22]), "+f"(d[23]), "+f"(d[24]), "+f"(d[25]), "+f"(d[26]), "+f"(d[27]), "+f"(d[28]), "+f"(d[29]), "+f"(d[30]), "+f"(d[31]), "+f"(d[32]), "+f"(d[33]), "+f"(d[34]), "+f"(d[35]), "+f"(d[36]), "+f"(d[37]), "+f"(d[38]), "+f"(d[39]), "+f"(d[40]), "+f"(d[41]), "+f"(d[42]), "+f"(d[43]), "+f"(d[44]), "+f"(d[45]), "+f"(d[46]), "+f"(d[47]), "+f"(d[48]), "+f"(d[49]), "+f"(d[50]), "+f"(d[51]), "+f"(d[52]), "+f"(d[53]), "+f"(d[54]), "+f"(d[55]), "+f"(d[56]), "+f"(d[57]), "+f"(d[58]), "+f"(d[59]), "+f"(d[60]), "+f"(d[61]), "+f"(d[62]), "+f"(d[63])
   : "l"(da), "l"(db), "r"(scale_d));
}
__device__ __forceinline__ void wgmma_n48(float (&d)[24], uint64_t da, uint64_t db, int scale_d) {
  asm volatile("{\n.reg .pred p;\nsetp.ne.b32 p, %26, 0;\n"
    "wgmma.mma_async.sync.aligned.m64n48k16.f32.bf16.bf16 {%0, %1, %2, %3, %4, %5, %6, %7, %8, %9, %10, %11, %12, %13, %14, %15, %16, %17, %18, %19, %20, %21, %22, %23}, %24, %25, p, 1, 1, 0, 0;\n}"
   : "+f"(d[0]), "+f"(d[1]), "+f"(d[2]), "+f"(d[3]), "+f"(d[4]), "+f"(d[5]), "+f"(d[6]), "+f"(d[7]), "+f"(d[8]), "+f"(d[9]), "+f"(d[10]), "+f"(d[11]), "+f"(d[12]), "+f"(d[13]), "+f"(d[14]), "+f"(d[15]), "+f"(d[16]), "+f"(d[17]), "+f"(d[18]), "+f"(d[19]), "+f"(d[20]), "+f"(d[21]), "+f"(d[22]), "+f"(d[23])
   : "l"(da), "l"(db), "r"(scale_d));
}

__device__ __forceinline__ void mma16816(float* d, uint32_t a0, uint32_t a1, uint32_t a2, uint32_t a3, uint32_t b0, uint32_t b1) {
  asm("mma.sync.aligned.m16n8k16.row.col.f32.bf16.bf16.f32 {%0,%1,%2,%3}, {%4,%5,%6,%7}, {%8,%9}, {%0,%1,%2,%3};"
               : "+f"(d[0]), "+f"(d[1]), "+f"(d[2]), "+f"(d[3]) : "r"(a0), "r"(a1), "r"(a2), "r"(a3), "r"(b0), "r"(b1));
}
__device__ __forceinline__ void ldsm4(uint32_t& r0, uint32_t& r1, uint32_t& r2, uint32_t& r3, uint32_t addr) {
  asm volatile("ldmatrix.sync.aligned.m8n8.x4.shared.b16 {%0,%1,%2,%3}, [%4];" : "=r"(r0), "=r"(r1), "=r"(r2), "=r"(r3) : "r"(addr) : "memory");
}
__device__ __forceinline__ void ldsm4t(uint32_t& r0, uint32_t& r1, uint32_t& r2, uint32_t& r3, uint32_t addr) {
  asm volatile("ldmatrix.sync.aligned.m8n8.x4.trans.shared.b16 {%0,%1,%2,%3}, [%4];" : "=r"(r0), "=r"(r1), "=r"(r2), "=r"(r3) : "r"(addr) : "memory");
}
__device__ __forceinline__ void stsm4(uint32_t addr, uint32_t r0, uint32_t r1, uint32_t r2, uint32_t r3) {
  asm volatile("stmatrix.sync.aligned.m8n8.x4.shared.b16 [%0], {%1,%2,%3,%4};" ::"r"(addr), "r"(r0), "r"(r1), "r"(r2), "r"(r3) : "memory");
}
__device__ __forceinline__ uint32_t lds16(uint32_t a) { uint16_t v; asm volatile("ld.shared.u16 %0, [%1];" : "=h"(v) : "r"(a) : "memory"); return v; }
template <typename T> __device__ __forceinline__ T lds(uint32_t a) {
  return *reinterpret_cast<const T*>(__cvta_shared_to_generic(a));
}
__device__ __forceinline__ void sts32(uint32_t a, uint32_t v) { asm volatile("st.shared.u32 [%0], %1;" ::"r"(a), "r"(v) : "memory"); }
__device__ __forceinline__ void sts16(uint32_t a, uint32_t v) { asm volatile("st.shared.u16 [%0], %1;" ::"r"(a), "h"((uint16_t)v) : "memory"); }
__device__ __forceinline__ void sts128(uint32_t a, uint32_t x, uint32_t y, uint32_t z, uint32_t w) {
  asm volatile("st.shared.v4.u32 [%0], {%1,%2,%3,%4};" ::"r"(a), "r"(x), "r"(y), "r"(z), "r"(w) : "memory");
}
__device__ __forceinline__ uint32_t pack2(float lo, float hi) {
  uint32_t r; asm("cvt.rn.bf16x2.f32 %0, %1, %2;" : "=r"(r) : "f"(hi), "f"(lo)); return r;
}
__device__ __forceinline__ float bf_lo(uint32_t v) { return __uint_as_float(v << 16); }
__device__ __forceinline__ float bf_hi(uint32_t v) { return __uint_as_float(v & 0xffff0000u); }
__device__ __forceinline__ float bf_round(float v) { return bf_lo(pack2(v, 0.f)); }
__device__ __forceinline__ float sqrt_approx(float v) { float r; asm("sqrt.approx.ftz.f32 %0, %1;" : "=f"(r) : "f"(v)); return r; }
__device__ __forceinline__ float rcp_approx(float v) { float r; asm("rcp.approx.ftz.f32 %0, %1;" : "=f"(r) : "f"(v)); return r; }
__device__ __forceinline__ uint4 ldg128(const void* p) { return __ldg(reinterpret_cast<const uint4*>(p)); }
__device__ __forceinline__ float warp_sum(float v) {
#pragma unroll
  for (int o = 16; o > 0; o >>= 1) v += __shfl_xor_sync(0xffffffffu, v, o);
  return v;
}
struct cf { float r, i; };
__device__ __forceinline__ cf cmul(cf a, cf b) { return {fmaf(a.r, b.r, -a.i * b.i), fmaf(a.r, b.i, a.i * b.r)}; }
__device__ __forceinline__ cf csqr(cf a) { return {fmaf(a.r, a.r, -a.i * a.i), (a.r + a.r) * a.i}; }
__device__ __forceinline__ cf cexp_at(float lr2, float li, float x) {
  float m; asm("ex2.approx.ftz.f32 %0, %1;" : "=f"(m) : "f"(lr2 * x));
  return {m * __cosf(li * x), m * __sinf(li * x)};
}
constexpr float GK = 2.f * 0.7978845608028654f;
__device__ __forceinline__ uint32_t gelu2(float y0, float y1) {
  uint32_t r;
  asm("{\n.reg .b32 y, z, t;\ncvt.rn.bf16x2.f32 y, %2, %1;\nmul.rn.bf16x2 z, y, y;\nmul.rn.bf16x2 z, z, %3;\n"
      "fma.rn.bf16x2 z, z, y, y;\ntanh.approx.bf16x2 t, z;\nfma.rn.bf16x2 %0, y, t, y;\n}"
      : "=r"(r) : "f"(y0), "f"(y1), "r"(0x3d903d90u));
  return r;
}

struct Frag { uint32_t a0, a1, a2, a3; };
__device__ __forceinline__ Frag tap_frag(uint32_t a) {
  Frag f = {lds<uint32_t>(a), lds<uint32_t>(a - 16), lds<uint32_t>(a + 16), 0};
  asm volatile("prmt.b32 %0, %1, %1, 0x3210;" : "=r"(f.a3) : "r"(f.a0));
  return f;
}
__device__ __forceinline__ uint32_t tap_base(uint32_t arr, uint32_t copy, int top, int lane) {
  return arr + ((lane >> 2) & 1) * copy + 4 * (top / 2 - (((lane >> 2) + 1) >> 1) + (lane & 3));
}
__device__ __forceinline__ void conv_near(float (&acc)[16][4], uint32_t taps, uint32_t xt, int rho0, int lane) {
#pragma unroll
  for (int j = 0; j < 16; j++) { acc[j][0] = acc[j][1] = acc[j][2] = acc[j][3] = 0.f; }
  uint32_t ka = tap_base(taps, KN_COPY, 528, lane) - 32 * rho0;
  int rr = (lane & 7) + 8 * (lane >> 4) - rho0;
  const uint32_t k1024 = lds<uint32_t>(taps + KB_OFF + 288) & 0xffffu;
  auto diag = [&](int d) { const int e = (lane >> 2) - 2 * (lane & 3) - d; return e == 0 ? k1024 : e == 1 ? k1024 << 16 : 0u; };
#pragma unroll 1
  for (int rho = rho0; rho < rho0 + 4; rho++, rr--, ka -= 32) {
    uint32_t X[16][2];
    const uint32_t xa = xt + 256 + rr * 32 + ((((lane >> 3) ^ (rr >> 2)) & 1) << 4);
    Frag f[4];
#pragma unroll
    for (int kap = 0; kap < 4; kap++) f[kap] = tap_frag(ka - 256 * kap);
#pragma unroll
    for (int i = 0; i < 8; i++) ldsm4(X[2 * i][0], X[2 * i][1], X[2 * i + 1][0], X[2 * i + 1][1], xa + i * 512);
#pragma unroll
      for (int jx = 0; jx < 16; jx++) {
#pragma unroll
        for (int kap = 0; kap < 4; kap++) if (jx + kap < 16) mma16816(acc[jx + kap], f[kap].a0, f[kap].a1, f[kap].a2, f[kap].a3, X[jx][0], X[jx][1]);
      }
    if (rho == 0) {
      const Frag e = tap_frag(ka - 1024);
#pragma unroll
      for (int j = 4; j < 16; j++) mma16816(acc[j], e.a0, e.a1, e.a2, e.a3, X[j - 4][0], X[j - 4][1]);
      const uint32_t d0 = diag(-5), d2 = diag(3);
#pragma unroll
      for (int j = 8; j < 16; j++) mma16816(acc[j], d0, 0u, d2, d0, X[j - 8][0], X[j - 8][1]);
    }
    if (rho == 7) {
      const uint32_t d1 = diag(3);
#pragma unroll
      for (int j = 7; j < 16; j++) mma16816(acc[j], 0u, d1, 0u, 0u, X[j - 7][0], X[j - 7][1]);
    }
  }
}
template <int DLO, int DHI, int NS>
__device__ __forceinline__ void conv_far(float (&acc)[13][4], uint32_t ka, uint32_t u, uint32_t zero, int lane) {
  uint32_t X[NS + 1][2];
  const uint32_t ua = u + 16 + (lane - 16) * 16;
#pragma unroll
  for (int i = 0; i < (NS + 1) / 2; i++)
    ldsm4t(X[2 * i][0], X[2 * i][1], X[2 * i + 1][0], X[2 * i + 1][1], i == 0 && lane < 15 ? zero : ua + i * 512);
#pragma unroll
  for (int d = DLO; d <= DHI; d++) {
    const Frag f = tap_frag(ka - 32 * d);
#pragma unroll
    for (int sg = 0; sg < NS; sg++)
      if (d + sg - 1 <= 15) mma16816(acc[d + sg - 4], f.a0, f.a1, f.a2, f.a3, X[sg][0], X[sg][1]);
  }
}
__device__ __forceinline__ uint32_t hadd2(uint32_t a, uint32_t b) { uint32_t r; asm("add.rn.bf16x2 %0, %1, %2;" : "=r"(r) : "r"(a), "r"(b)); return r; }

__device__ __noinline__ void layer_norm(uint32_t sb, int t2, int cid, uint32_t ep) {
      const int tid = t2, lane = t2 & 31;
      mbar_wait(sb + BAR_OFF + 8 * B_XR, 0);
      float f[32], s0 = 0.f, s1 = 0.f;
      const int row = t2 >> 4;
      uint4 ld[4];
#pragma unroll
      for (int i = 0; i < 4; i++) ld[i] = lds<uint4>(sb + LN_OFF + t2 * 16 + row * 768 + i * 256);
#pragma unroll
      for (int k = 0; k < 16; k++) { const uint32_t u = (&ld[k >> 2].x)[k & 3]; f[2 * k] = bf_lo(u); f[2 * k + 1] = bf_hi(u); s0 += f[2 * k]; s1 += f[2 * k + 1]; }
      float mean = (s0 + s1) * (1.f / 32.f), q0 = 0.f, q1 = 0.f;
#pragma unroll
      for (int k = 0; k < 32; k += 2) { const float d0 = f[k] - mean, d1 = f[k + 1] - mean; q0 = fmaf(d0, d0, q0); q1 = fmaf(d1, d1, q1); }
      float m2s = q0 + q1;
#pragma unroll
      for (int o = 1; o < 16; o <<= 1) {
        const float mo = __shfl_xor_sync(0xffffffffu, mean, o), qo = __shfl_xor_sync(0xffffffffu, m2s, o);
        const float dl = mean - mo;
        m2s = fmaf(dl * dl, 16.f * o, m2s + qo);
        mean = 0.5f * (mean + mo);
      }
      const float var = m2s * (1.f / D_);
      const float mb = bf_round(mean), sd1 = bf_round(sqrt_approx(bf_round(bf_round(var) + 1e-5f))), rs1 = rcp_approx(sd1);
      const float m2b = bf_round((mean - mb) * rs1), sd2 = bf_round(sqrt_approx(bf_round(bf_round(var * rs1 * rs1) + 1e-5f)));
      const float sh = -mb * rs1;
      const uint32_t ra = sb + LN_OFF + row * 1024 + (((tid & 15) ^ (((row >> 2) << 1) | (row & 1))) << 4);
#pragma unroll
      for (int i = 0; i < 4; i++)
        sts128(ra + 256 * i, pack2(fmaf(f[8 * i], rs1, sh), fmaf(f[8 * i + 1], rs1, sh)), pack2(fmaf(f[8 * i + 2], rs1, sh), fmaf(f[8 * i + 3], rs1, sh)),
               pack2(fmaf(f[8 * i + 4], rs1, sh), fmaf(f[8 * i + 5], rs1, sh)), pack2(fmaf(f[8 * i + 6], rs1, sh), fmaf(f[8 * i + 7], rs1, sh)));
      if ((lane & 14) == 0)
        st_tagged(reinterpret_cast<uint2*>(&g_stats[cid * 16 + row]) + (lane & 1), (lane & 1) ? sd1 * sd2 : -fmaf(m2b, sd1, mb), ep);
      asm volatile("bar.arrive 9, 352;" ::: "memory");
}

__device__ __forceinline__ void box_filter(uint32_t sb, int ww, int ck, int end) {
      const uint32_t xt = sb + XT_OFF + ww * XT_CH, U = sb + U_OFF + ww * U_CH;
      mbar_wait(sb + BAR_OFF + 8 * B_XT, 0);
      mbar_wait(sb + BAR_OFF + 8 * B_KRDY, 0);
#pragma unroll 1
      for (; ck < end; ck += 32) {
        auto xc = [&](int k) { return lds<uint4>(xt + 256 + ((k ^ ((k >> 3) & 1)) << 4)); };
        const uint4 p = xc(ck - 1), q = xc(ck), r = xc(ck + 1);
        const uint32_t w[12] = {p.x, p.y, p.z, p.w, q.x, q.y, q.z, q.w, r.x, r.y, r.z, r.w};
        uint32_t o[11], b3[6], b5[4], b7[4], b9[4];
#pragma unroll
        for (int i = 1; i < 10; i++) o[i] = __byte_perm(w[i], w[i + 1], 0x5432);
#pragma unroll
        for (int i = 0; i < 6; i++) b3[i] = hadd2(hadd2(o[i + 1], o[i + 2]), w[i + 2]);
#pragma unroll
        for (int i = 0; i < 4; i++) {
          b5[i] = hadd2(b3[i + 2], hadd2(w[i + 3], w[i + 5]));
          b7[i] = hadd2(b5[i], hadd2(o[i + 2], o[i + 5]));
          b9[i] = hadd2(b7[i], hadd2(w[i + 2], w[i + 6]));
        }
        const uint32_t ua = U + 16 + ck * 16;
        sts128(ua, b5[0], b5[1], b5[2], b5[3]); sts128(ua + UA_LEN, b3[0], b3[1], b3[2], b3[3]);
        if (ck < 128) { sts128(ua + 2 * UA_LEN, b9[0], b9[1], b9[2], b9[3]); sts128(ua + 2 * UA_LEN + UB_LEN, b7[0], b7[1], b7[2], b7[3]); }
      }
}

struct Params {
  const __nv_bfloat16 *x, *a_re, *a_im, *b_re, *b_im, *c_re, *c_im, *log_dt, *dskip, *w1, *b1, *w2, *b2;
  __nv_bfloat16* out;
};

__global__ void __cluster_dims__(2, 1, 1) __launch_bounds__(512, 1)
fused_kernel(const Params P, const __grid_constant__ CUtensorMap tmX1, const __grid_constant__ CUtensorMap tmW1s, const __grid_constant__ CUtensorMap tmW1h,
             const __grid_constant__ CUtensorMap tmHs, const __grid_constant__ CUtensorMap tmHh, const __grid_constant__ CUtensorMap tmHld,
             const __grid_constant__ CUtensorMap tmW2, const __grid_constant__ CUtensorMap tmXe, const __grid_constant__ CUtensorMap tmZ,
             const __grid_constant__ CUtensorMap tmXT) {
#define FRESH_SB() uint32_t sb; asm volatile("mov.u32 %0, %%cluster_ctarank;" : "=r"(sb)); sb = (sb << 24) + 1024
  FRESH_SB();
  if (sb != smem_u32(smem_raw)) __trap();
#define BAR(i) (sb + BAR_OFF + 8u * (i))
  const int tid = threadIdx.x, warp = tid >> 5, lane = tid & 31, wg = tid >> 7, ww = warp & 3, g = lane >> 2, c = lane & 3;
  const int cid = blockIdx.x, ch = cid * 4 + ww;
  const int po = ch * NM_ + wg * 32 + lane;
  auto ldu16 = [](const __nv_bfloat16* p) { return (uint32_t)__ldg(reinterpret_cast<const unsigned short*>(p)); };
  uint32_t pr[7];
  unsigned ep;
  auto load_params = [&]() {
    pr[0] = ldu16(P.a_re + po); pr[1] = ldu16(P.a_im + po); pr[2] = ldu16(P.b_re + po); pr[3] = ldu16(P.b_im + po);
    pr[4] = ldu16(P.c_re + po); pr[5] = ldu16(P.c_im + po); pr[6] = ldu16(P.log_dt + ch);
    asm volatile("ld.relaxed.gpu.global.u32 %0, [%1];" : "=r"(ep) : "l"(&g_cnt[C_Z]) : "memory");
  };
  load_params();
  const int cq_ = blockIdx.x >> 1, rank = blockIdx.x & 1, q7 = ((cq_ - 36) * 37) >> 8;
  const int grp = cq_ < 4 ? 0 : cq_ < 36 ? (cq_ - 4) & 7 : cq_ - 35 - 7 * q7, pp = cq_ < 4 ? 4 + cq_ : cq_ < 36 ? (cq_ - 4) >> 3 : 4 + q7;
  const int rb1 = 2 * grp + rank, js = pp;
  const int rb = 2 * grp + (pp >> 2), cb = pp & 3;
  const int w1g = 7 * (js >> 1) + 4 * (js & 1), w1h = 14 * (js >> 1) + 6 + (js & 1);
  const int oc = cb * 128 + rank * 64;
  if (warp == 12) {
    if (elect()) {
      prefetch_map(&tmX1); prefetch_map(&tmW1s); prefetch_map(&tmW1h);
      for (int i = 0; i < 6; i++) { mbar_init(BAR(B_FULL1 + i), 1); mbar_init(BAR(B_EMPTY1 + i), 16); }
    }
    __syncwarp();
  }
  if (warp == 13) {
    if (elect()) {
      for (int i = 0; i < 4; i++) { mbar_init(BAR(B_FULL2 + i), 2); mbar_init(BAR(B_EMPTY2 + i), 8); }
      mbar_init(BAR(B_TAB), 2); mbar_init(BAR(B_HFREE), 2); mbar_init(BAR(B_KG), 8); mbar_init(BAR(B_G1), 8);
      mbar_init(BAR(B_HST), 4); mbar_init(BAR(B_HST + 1), 4); mbar_init(BAR(B_BASE), 4); mbar_init(BAR(B_KRDY), 4);
    }
    __syncwarp();
  }
  if (warp == 14) {
    if (elect()) {
      mbar_init(BAR(B_XR), 1);
      fence_async_smem();
      mbar_expect(BAR(B_XR), 16384);
      bulk_ld(sb + LN_OFF, P.x + cid * 16 * D_, 16384, BAR(B_XR));
      for (int i = B_XT; i <= B_RED; i++) mbar_init(BAR(i), 1);
      mbar_init(BAR(B_LN), 3); mbar_init(BAR(B_CONV), 12);
      mbar_expect(BAR(B_RED), 16384);
    }
    __syncwarp();
  }
  asm volatile("fence.mbarrier_init.release.cluster;" ::: "memory");
  asm volatile("barrier.cluster.arrive.relaxed.aligned;" ::: "memory");
  const uint32_t sh16 = 16 + (uint32_t)(clock64() >> 63);
  if (tid == 480) l2_prefetch(P.w1 + cid * 7168 + ((pr[6] << (sh16 - 16)) >> 16), 14336);
    auto load_stage1 = [&](uint32_t sb, int kt, int st) {
      const uint32_t dst = sb + st * S1_BYTES, bar = BAR(B_FULL1 + st);
      mbar_expect(bar, S1_BYTES);
      tma_ld2(dst, &tmX1, kt * 32, rb1 * 128, bar);
      tma_ld3_mc(dst + 8192 + rank * 8192, &tmW1s, 0, kt * 32, w1g + 2 * rank, bar);
      tma_ld3_mc(dst + 12288 + rank * 8192, rank ? &tmW1h : &tmW1s, 0, kt * 32, rank ? w1h : w1g + 1, bar);
    };
  {
#pragma unroll
    for (int k = 0; k < 7; k++) pr[k] <<= sh16 - 16;
    const float dt = bf_round(__expf(bf_lo(pr[6])));
    const float lr2 = (dt * bf_lo(pr[0])) * 1.4426950408889634f, lit = dt * bf_lo(pr[1]);
    const cf CB = cmul({bf_lo(pr[4]), bf_lo(pr[5])}, {dt * bf_lo(pr[2]), dt * bf_lo(pr[3])});
    const uint32_t buf = sb + (wg < 2 ? SSM_OFF : KG_HI - 2 * KG_BUF) + wg * KG_BUF;
    const int m = lane >> 3, r8 = lane & 7;
    const uint32_t bufA = (warp == 8 || warp == 9 ? sb + AZ_OFF : buf) + ww * 4096 + m * 1024, bufB = buf + 16384 + ww * 3072;
    const cf z1 = cexp_at(lr2, -lit, 1.f), z8 = cexp_at(lr2, lit, 8.f), z64 = cexp_at(lr2, lit, 64.f), V = cexp_at(lr2, -lit, 256.f);
    const cf z2 = csqr(z1), V2 = csqr(V), V3 = cmul(V2, V);
    cf a0 = CB, a1 = cmul(a0, z64), a2 = cmul(a1, z64), a3 = cmul(a2, z64), p0 = {1.f, 0.f}, p4 = csqr(z2), p1 = V, p2 = csqr(V2);
    const cf q2 = cmul(V2, p4), q3 = cmul(V3, p4);
    stsm4(bufB + 2048 + m * 128 + ((r8 ^ m) << 4), pack2(V2.r, V2.i), pack2(q2.r, q2.i), pack2(V3.r, V3.i), pack2(q3.r, q3.i));
#pragma unroll
    for (int t = 0; t < 8; t++) {
      const uint32_t off = t * 128 + ((r8 ^ t) << 4);
      stsm4(bufA + off, pack2(a0.r, a0.i), pack2(a1.r, a1.i), pack2(a2.r, a2.i), pack2(a3.r, a3.i));
      a0 = cmul(a0, z8); a1 = cmul(a1, z8); a2 = cmul(a2, z8); a3 = cmul(a3, z8);
      if (t < 4) {
        stsm4(bufB + m * 512 + (off ^ ((m & 1) << 6)), pack2(p0.r, p0.i), pack2(p4.r, p4.i), pack2(p1.r, p1.i), pack2(p2.r, p2.i));
        p0 = cmul(p0, z1); p4 = cmul(p4, z1); p1 = cmul(p1, z2); p2 = cmul(p2, V);
      }
    }
    ep = ep / NCTA + (sh16 - 15);
    const float k2048 = warp_sum(fmaf(CB.r, p2.r, CB.i * p2.i));
    if (lane == 0) sts32(sb + K2_OFF + warp * 4, __float_as_uint(k2048));
    fence_async_smem();
    asm volatile("barrier.cluster.wait.acquire.aligned;" ::: "memory");
    if (wg != 2) asm volatile("bar.arrive 2, 512;" ::: "memory"); else bar_sync(2, 512);
  }

  if (wg >= 2) {
  if (wg == 3) {
    FRESH_SB();
    asm volatile("setmaxnreg.dec.sync.aligned.u32 64;");
    if (warp > 12) {
      const int cq = cid < 112 ? cid : 0, r0 = (tid - 416) >> 3;
      const __nv_bfloat16* wp = P.w1 + ((cq & 3) * 128 + r0) * F_ + (cq >> 2) * 64 + (tid & 7) * 8;
      float cs[8];
#pragma unroll
      for (int k = 0; k < 8; k++) cs[k] = 0.f;
#pragma unroll 1
      for (int i = 0; i < 2; i++) {
        uint4 wv[6];
#pragma unroll
        for (int r = 0; r < 6; r++) wv[r] = r0 + 72 * i + 12 * r < 128 ? ldg128(wp + (72 * i + 12 * r) * F_) : make_uint4(0, 0, 0, 0);
#pragma unroll
        for (int r = 0; r < 6; r++) {
#pragma unroll
          for (int k = 0; k < 4; k++) { cs[2 * k] += bf_lo((&wv[r].x)[k]); cs[2 * k + 1] += bf_hi((&wv[r].x)[k]); }
        }
      }
#pragma unroll
      for (int k = 0; k < 4; k++) { const bool up = lane & 8; const float snd = up ? cs[k] : cs[k + 4], kp = up ? cs[k + 4] : cs[k]; cs[k] = kp + __shfl_xor_sync(0xffffffffu, snd, 8); }
#pragma unroll
      for (int k = 0; k < 2; k++) { const bool up = lane & 16; const float snd = up ? cs[k] : cs[k + 2], kp = up ? cs[k + 2] : cs[k]; cs[k] = kp + __shfl_xor_sync(0xffffffffu, snd, 16); }
      asm volatile("st.shared.v2.f32 [%0], {%1,%2};" ::"r"(sb + WS_OFF + (tid - 416) * 8), "f"(cs[0]), "f"(cs[1]) : "memory");
      bar_sync(11, 96);
      if (warp == 15 && cid < 112) {
        float2 s = make_float2(0.f, 0.f);
#pragma unroll
        for (int k = 0; k < 3; k++) { const float2 v = lds<float2>(sb + WS_OFF + k * 256 + lane * 8); s.x += v.x; s.y += v.y; }
        uint2* p = &g_w1sum[((cid >> 2) * 64 + (lane & 7) * 8 + ((lane >> 3) & 1) * 4 + (lane >> 4) * 2) * 4 + (cid & 3)];
        st_tagged(p, s.x, ep); st_tagged(p + 4, s.y, ep);
      }
    }
    if (warp > 12) {
      bar_sync(9, 352);
      const int m = lane >> 3, rho = lane & 7;
      const uint32_t la = sb + LN_OFF + (4 * (rho >> 1) + (rho & 1) + 2 * (m & 1)) * 1024;
      const uint32_t ta = sb + TR_OFF + g * 32 + ((((lane >> 1) ^ (cid >> 2)) & 1) << 4) + ((lane & 1) << 3);
#pragma unroll 4
      for (int dg = ww - 1; dg < 32; dg += 3) {
        uint32_t r[4];
        ldsm4t(r[0], r[1], r[2], r[3], la + (dg >> 2) * 128 + (((2 * (dg & 3) + (m >> 1)) ^ rho) << 4));
        asm volatile("st.shared.v2.u32 [%0], {%1,%2};" ::"r"(ta + dg * 512), "r"(r[0]), "r"(r[1]) : "memory");
        asm volatile("st.shared.v2.u32 [%0], {%1,%2};" ::"r"(ta + dg * 512 + 256), "r"(r[2]), "r"(r[3]) : "memory");
      }
      fence_async_smem();
      __syncwarp();
      if (lane == 0) mbar_arrive(BAR(B_LN));
    }
    if (warp == 12) {
#pragma unroll 1
      for (int kt = 0; kt < 16; kt++) {
        const int st = kt % S1_N;
        if (kt >= 4) mbar_wait(BAR(kt < 6 ? B_KG : B_EMPTY1 + st), kt >= 12);
        if (elect()) load_stage1(sb, kt, st);
        __syncwarp();
      }
    } else if (warp == 15) {
      mbar_wait(BAR(B_LN), 0);
      if (lane == 0) {
        asm volatile("cp.async.bulk.global.shared::cta.bulk_group [%0], [%1], 16384;" ::"l"(g_xnT + cid * 16 * D_), "r"(sb + TR_OFF) : "memory");
        bulk_commit();
        bulk_wait0(); fence_async_global();
        signal_done(&g_cnt[C_LN]);
      }
      __syncwarp();
#pragma unroll
      for (int w = 0; w < 2; w++) sts128(sb + XT_OFF + (2 * w + (lane >> 4)) * XT_CH + (lane & 15) * 16, 0, 0, 0, 0);
      fence_async_smem();
      __syncwarp();
      if (lane == 0) {
        l2_prefetch(P.w2 + cid * 7168, 14336);
        wait_gpu(&g_cnt[C_LN], ep * NCTA);
        fence_async_global();
        mbar_expect(BAR(B_XT), 4 * 4096);
#pragma unroll 1
        for (int w = 0; w < 4; w++) tma_ld3(sb + XT_OFF + w * XT_CH + 256, &tmXT, 0, cid * 4 + w, 0, BAR(B_XT));
      }
    } else {
      mbar_wait(BAR(B_KG), 0);
#pragma unroll 1
      for (int t2 = tid - 416; t2 < 128; t2 += 64) {
      const int c0 = js * 224 + (t2 + 32 * (js & 1)) % 224, c1 = js * 224 + (t2 + 96 + 32 * (js & 1)) % 224;
      const uint32_t b0 = ldu16(P.b1 + c0), b1 = ldu16(P.b1 + c1);
      uint4 r, p0, p1, q0, q1;
#pragma unroll 1
      for (int it = 0;; it++) {
        r = ld_tagged2(&g_stats[rb1 * 128 + t2]);
        p0 = ld_tagged2(&g_w1sum[c0 * 4]); p1 = ld_tagged2(&g_w1sum[c0 * 4 + 2]);
        q0 = ld_tagged2(&g_w1sum[c1 * 4]); q1 = ld_tagged2(&g_w1sum[c1 * 4 + 2]);
        if ((((r.y ^ ep) | (r.w ^ ep) | (p0.y ^ ep)) | ((p0.w ^ ep) | (p1.y ^ ep) | (p1.w ^ ep)) | ((q0.y ^ ep) | (q0.w ^ ep) | (q1.y ^ ep)) | (q1.w ^ ep)) == 0) break;
        if (it > (1 << 20)) __trap();
        __nanosleep(256);
      }
      sts128(sb + AZ_OFF + t2 * 16, 0, 0, 0, 0);
      const float u = __uint_as_float(r.x), v = __uint_as_float(r.z), uh = bf_round(u), vh = bf_round(v);
      sts128(sb + AX_OFF + t2 * 16, pack2(uh, uh), pack2(u - uh, vh), pack2(v - vh, 0.f), 0);
      sts32(sb + SC_OFF + t2 * 4, __float_as_uint(0.5f * GK * rcp_approx(v)));
      const float s0 = (__uint_as_float(p0.x) + __uint_as_float(p0.z)) + (__uint_as_float(p1.x) + __uint_as_float(p1.z)), h0 = bf_round(s0);
      const float s1 = (__uint_as_float(q0.x) + __uint_as_float(q0.z)) + (__uint_as_float(q1.x) + __uint_as_float(q1.z)), h1 = bf_round(s1);
      sts128(sb + BX_OFF + t2 * 16, pack2(h0, s0 - h0), pack2(h0, bf_lo(b0)), b0, 0);
      sts128(sb + BX_OFF + (t2 + 96) * 16, pack2(h1, s1 - h1), pack2(h1, bf_lo(b1)), b1, 0);
      }
      fence_async_smem();
      __syncwarp();
      if (lane == 0) mbar_arrive(BAR(B_TAB));
    }
    box_filter(sb, ww, lane + 95, 192);
    asm volatile("bar.arrive %0, 64;" ::"r"(12 + ww) : "memory");
    if (warp == 13 || warp == 14) {
      if (elect()) {
        {
          const int hf = warp - 13;
          mbar_wait(BAR(B_HST + hf), 0);
#pragma unroll 1
          for (int i = 0; i < 4; i++) {
            tma_st3(i == 3 ? &tmHh : &tmHs, 0, rb1 * 128 + hf * 64, i == 3 ? w1h : w1g + i, sb + hf * 32768 + i * 8192);
          }
          bulk_commit();
          bulk_wait_read0(); mbar_arrive(BAR(B_HFREE));
          bulk_wait0(); fence_async_global();
          signal_done(&g_cnt[C_H + 32 * (rb1 * 2 + (js >> 2))]);
        }
        if (warp == 14) {
          mbar_wait(BAR(B_CONV), 0);
          asm volatile("cp.async.bulk.global.shared::cta.bulk_group [%0], [%1], 16384;" ::"l"(g_zT + cid * 4 * L_), "r"(sb + ST_OFF) : "memory");
          bulk_commit();
          uint32_t remote;
          asm volatile("mapa.shared::cluster.u32 %0, %1, %2;" : "=r"(remote) : "r"(BAR(B_PFREE)), "r"(rank ^ 1));
          mbar_arrive_remote_light(remote);
          bulk_wait0(); fence_async_global();
          signal_done(&g_cnt[C_Z]);
          mbar_expect(BAR(B_EPI), 32768);
          tma_ld2(sb + ST_OFF, &tmXe, oc, rb * 128, BAR(B_EPI));
          wait_gpu(&g_cnt[C_Z], ep * NCTA);
          fence_async_global();
          tma_ld3(sb + ZT_OFF, &tmZ, 0, oc, rb * 2, BAR(B_EPI));
        }
      }
    }
    if (warp == 12 || warp == 15) {
      const bool is_a = warp == 12;
      mbar_wait(BAR(B_G1), 0);
      if (elect()) {
        if (is_a) {
          wait_gpu(&g_cnt[C_H + 32 * (rb * 2 + rank)], ep * 8);
          fence_async_global();
        }
#pragma unroll 1
        for (int it = 0; it < 14; it++) {
          const int s = it & 3;
          if (it >= 4) mbar_wait(BAR(B_EMPTY2 + s), ((it >> 2) - 1) & 1);
          if (it == 2) mbar_wait(BAR(B_HFREE), 0);
          const uint32_t dst = sb + RING_BYTES - S2_BYTES * (s + 1), bar = BAR(B_FULL2 + s);
          mbar_expect(bar, S2_BYTES / 2);
          if (is_a) {
            tma_ld2(dst, &tmHld, rank * 896 + it * 64, rb * 128, bar);
          } else {
#pragma unroll 1
            for (int q = 0; q < 2; q++) tma_ld3(dst + 16384 + q * 8192, &tmW2, 0, rank * 896 + it * 64, cb * 2 + (rank ^ q), bar);
          }
        }
      }
    }
  } else {
    FRESH_SB();
    uint32_t dsk = ldu16(P.dskip + ch);
    {
      float kacc[2][24];
      const uint64_t da = mk_desc(sb + SSM_OFF, 16, 1024, 1);
      WG_FENCE();
#pragma unroll
      for (int i = 0; i < 16; i++) {
        const int off = (((i < 8 ? 0 : (int)KG_HI - (int)SSM_OFF) + ((i >> 2) & 1) * (int)KG_BUF) >> 4) + 2 * (i & 3);
        wgmma_n48(kacc[0], da + off + ((i >> 2) == 2 ? ((int)AZ_OFF - (int)KG_HI) >> 4 : 0), da + 1024 + off, i != 0);
        wgmma_n48(kacc[1], da + 512 + off, da + 1024 + 384 + off, i != 0);
      }
      WG_COMMIT();
      WG_WAIT(0);
      pin(kacc[0]); pin(kacc[1]);
      if (lane == 0) {
        uint32_t remote;
        asm volatile("mapa.shared::cluster.u32 %0, %1, %2;" : "=r"(remote) : "r"(BAR(B_KG)), "r"(rank ^ 1));
        mbar_arrive(BAR(B_KG)); mbar_arrive_remote_light(remote);
      }
      bar_sync(3, 128);
      const int j = 16 * (ww & 1) + g;
      const uint32_t t1 = c < 2 ? 2 * (256 + 2 * c + 4 * j) : 2 * (384 + 64 * c + j), t1e = c < 2 ? 2 : 64, t1h = c < 2 ? 64 : 16;
#pragma unroll
      for (int i = 0; i < 4; i++) {
        const int hh = i & 1;
        const uint32_t T = sb + KD_OFF + ((i & 2) + (ww >> 1)) * KD_CH;
        float v[6];
#pragma unroll
        for (int k = 0; k < 6; k++) v[k] = (ww & 2) ? kacc[i >> 1][12 + 4 * (k >> 1) + 2 * hh + (k & 1)] : kacc[i >> 1][4 * (k >> 1) + 2 * hh + (k & 1)];
        sts32(T + 2 * (2 * c + 8 * j) + hh * 128, pack2(v[0], v[1]));
        const uint32_t pk = pack2(v[2], v[3]);
        sts16(T + t1 + hh * t1h, pk); sts16(T + t1 + hh * t1h + t1e, pk >> 16);
        if (c < 2) sts32(T + 2 * (384 + 64 * c + 2 * j) + hh * 32, pack2(v[4], v[5]));
      }
    }
    float k1024;
    layer_norm(sb, tid - 128, cid, ep);
    {
      const uint32_t T = sb + KD_OFF + ww * KD_CH;
      if (lane == 0) {
        const uint32_t k2 = sb + K2_OFF + ww * 4;
        sts16(T + 2 * 640, pack2((lds<float>(k2) + lds<float>(k2 + 16)) + (lds<float>(k2 + 32) + lds<float>(k2 + 48)), 0.f));
      }
      bar_sync(3, 128);
      const uint32_t taps = sb + SSM_OFF + ww * TAP_CH, E = taps + lane * 16, O = E + KN_COPY;
      auto P2 = [](uint32_t lo, uint32_t hi) { return __byte_perm(lo, hi, 0x5410); };
      k1024 = bf_lo(lds16(T + 2 * 512));
      {
        uint32_t v0 = lds16(T + 2 * (384 - 4 * lane));
        uint2 q = lds<uint2>(T + 2 * (380 - 4 * lane));
        if (lane == 0) { q.y = pack2(bf_lo(q.y), bf_hi(q.y) - bf_lo(v0)); v0 = 0; }
        const uint32_t v22 = __byte_perm(q.y, 0, 0x1010);
        sts128(E + 32, P2(v0, v0), __byte_perm(q.y, 0, 0x1032), v22, __byte_perm(q.x, 0, 0x1032));
        sts128(O + 32, __byte_perm(v0, q.y, 0x7610), v22, __byte_perm(q.y, q.x, 0x7610), __byte_perm(q.x, 0, 0x1010));
      }
      {
        const uint32_t v0 = lds16(T + 2 * (256 - 8 * lane));
        uint4 q = lds<uint4>(T + 2 * (248 - 8 * lane));
        asm volatile("" : "+r"(dsk));
        if (lane == 31) q.x = (q.x & 0xffff0000u) | (pack2(bf_lo(q.x) + bf_lo(dsk), 0.f) & 0xffffu);
        sts128(E + 544, __byte_perm(v0, q.w, 0x7610), __byte_perm(q.w, q.z, 0x7610), __byte_perm(q.z, q.y, 0x7610), __byte_perm(q.y, q.x, 0x7610));
        sts128(O + 544, __byte_perm(q.w, 0, 0x1032), __byte_perm(q.z, 0, 0x1032), __byte_perm(q.y, 0, 0x1032), __byte_perm(q.x, 0, 0x1032));
        if (lane >= 28) {
          const uint32_t a = taps + (lane == 28 ? 67 : lane == 31 ? 66 : lane - 29) * 16;
          sts128(a, lane == 31 ? q.x & 0xffffu : 0u, 0, 0, 0); sts128(a + KN_COPY, 0, 0, 0, 0);
        }
      }
#pragma unroll 1
      for (int w = lane; w < 128; w += 32) {
        const bool hi = w >= 48;
        const int i0 = hi ? 272 - 2 * (w - 48) : 144 - 2 * w;
        uint32_t a[3], b[3];
#pragma unroll
        for (int k = 0; k < 3; k++) {
          const int i = i0 - k;
          uint32_t v = 0;
          if (hi ? (i >= 128 && i <= 256) : (i >= 64 && i < 128)) v = hi ? lds16(T + 2 * (384 + i)) << (16 * (k & 1)) : lds<uint32_t>(T + 2 * (256 + 2 * i));
          if (!hi && i == 127) v = pack2(bf_lo(v), bf_hi(v) - k1024);
          a[k] = v & 0xffffu; b[k] = v >> 16;
        }
        const uint32_t dst = taps + (hi ? KB_OFF + (w - 48) * 4 : KA_OFF + w * 4), cp = hi ? KB_COPY : KA_COPY;
        sts32(dst, P2(a[0], a[1])); sts32(dst + cp, P2(a[1], a[2])); sts32(dst + 2 * cp, P2(b[0], b[1])); sts32(dst + 3 * cp, P2(b[1], b[2]));
      }
      __syncwarp();
      if (lane == 0) mbar_arrive(BAR(B_KRDY));
    }
    mbar_wait(BAR(B_XT), 0);
    {
      const uint32_t xt = sb + XT_OFF + ww * XT_CH, U = sb + U_OFF + ww * U_CH;
      box_filter(sb, ww, lane - 1, 95);
      bar_sync(12 + ww, 64);
      float acc[13][4];
#pragma unroll
      for (int j = 0; j < 13; j++) { acc[j][0] = acc[j][1] = acc[j][2] = acc[j][3] = 0.f; }
      const uint32_t taps = sb + SSM_OFF + ww * TAP_CH;
#pragma unroll 1
      for (int h = 0; h < 2; h++) {
        conv_far<4, 8, 13>(acc, tap_base(taps + KA_OFF + h * 2 * KA_COPY, KA_COPY, 144, lane), U + h * UA_LEN, xt, lane);
        conv_far<8, 16, 9>(acc, tap_base(taps + KB_OFF + h * 2 * KB_COPY, KB_COPY, 272, lane), U + 2 * UA_LEN + h * UB_LEN, xt, lane);
      }
      __syncwarp();
      sts128(U + lane * 16, 0, 0, 0, 0);
      if (lane < 16) sts128(U + 512 + lane * 16, 0, 0, 0, 0);
#pragma unroll
      for (int j = 0; j < 13; j += 2) {
        const int j1 = j < 12 ? j + 1 : j;
        stsm4(U + 768 + (lane < 16 ? j : j1) * 256 + (lane & 15) * 16, pack2(acc[j][0], acc[j][1]), pack2(acc[j][2], acc[j][3]),
              pack2(acc[j1][0], acc[j1][1]), pack2(acc[j1][2], acc[j1][3]));
      }
      asm volatile("bar.arrive %0, 96;" ::"r"(5 + ww) : "memory");
    }
    if (lane == 0) mbar_arrive(BAR(B_CONV));
    {
      const int mi = lane >> 3, r8 = lane & 7;
      mbar_wait(BAR(B_CONV), 0);
      sts32(sb + K2_OFF + lane * 4, __ldg(reinterpret_cast<const uint32_t*>(P.b2 + oc) + lane));
      __syncwarp();
      mbar_wait(BAR(B_EPI), 0);
#pragma unroll 1
      for (int h = 0; h < 2; h++) {
#pragma unroll 1
        for (int q = 0; q < 4; q++) {
          uint32_t xx[4], zz[4];
          const uint32_t bb[2] = {lds<uint32_t>(sb + K2_OFF + q * 32 + c * 4), lds<uint32_t>(sb + K2_OFF + q * 32 + 16 + c * 4)};
          ldsm4(xx[0], xx[1], xx[2], xx[3], sb + ST_OFF + (h * 64 + ww * 16 + (lane & 15)) * 128 + (((2 * q + (mi >> 1)) ^ r8) << 4));
          ldsm4t(zz[0], zz[1], zz[2], zz[3], sb + ZT_OFF + h * 8192 + (16 * q + 8 * (mi >> 1) + r8) * 128 + (((2 * ww + (mi & 1)) ^ r8) << 4));
#pragma unroll
          for (int k = 0; k < 4; k++)
            xx[k] = pack2(bf_lo(xx[k]) + bf_lo(zz[k]) + bf_lo(bb[k >> 1]), bf_hi(xx[k]) + bf_hi(zz[k]) + bf_hi(bb[k >> 1]));
          sts128(sb + BASE_OFF + q * 4096 + (h * 128 + (tid & 127)) * 16, xx[0], xx[1], xx[2], xx[3]);
        }
      }
      __syncwarp();
      if (lane == 0) mbar_arrive(BAR(B_BASE));
    }
  }
  } else {
    FRESH_SB();
    if (wg == 0) layer_norm(sb, tid, cid, ep);
    asm volatile("setmaxnreg.inc.sync.aligned.u32 160;");
    uint32_t rsb;
    asm volatile("mapa.shared::cluster.u32 %0, %1, %2;" : "=r"(rsb) : "r"(sb), "r"(rank ^ 1));
    {
      float accA[64], accB[48];
      int st = 0, prev = 0;
#pragma unroll 1
      for (int kt = 0; kt < 16; kt++) {
        mbar_wait(BAR(B_FULL1 + st), kt >= 6 && kt < 12);
        const uint64_t da = mk_desc(sb + st * S1_BYTES + wg * 4096, 16, 512, 2);
        const uint64_t db = mk_desc(sb + st * S1_BYTES + 8192, 4096, 1024, 1);
        WG_FENCE();
#pragma unroll
        for (int kk = 0; kk < 2; kk++) {
          wgmma_n128_tb(accA, da + 2 * kk, db + 128 * kk, (kt | kk) != 0);
          wgmma_n96_tb(accB, da + 2 * kk, db + 512 + 128 * kk, (kt | kk) != 0);
        }
        WG_COMMIT();
        WG_WAIT(1);
        if (kt > 0 && lane == 0) { mbar_arrive(BAR(B_EMPTY1 + prev)); mbar_arrive_remote_light(rsb + BAR_OFF + 8 * (B_EMPTY1 + prev)); }
        prev = st;
        st = st == S1_N - 1 ? 0 : st + 1;
      }
      mbar_wait(BAR(B_TAB), 0);
      {
        const uint64_t da = mk_desc(sb + AZ_OFF + wg * 1024, 2048, 128, 0), db = mk_desc(sb + BX_OFF, 0, 128, 0);
        WG_FENCE();
        wgmma_n128(accA, da, db, 1);
        wgmma_n96(accB, da, db + 128, 1);
        WG_COMMIT();
      }
      WG_WAIT(0);
      pin(accA); pin(accB);
      if (lane == 0) mbar_arrive(BAR(B_G1));
      bar_sync(1, 256);
      const uint32_t hw = sb + wg * 32768 + ww * 2048;
      {
        const uint32_t hrow = hw + (lane & 15) * 128;
        const float s0 = lds<float>(sb + SC_OFF + (wg * 64 + ww * 16 + g) * 4), s1 = lds<float>(sb + SC_OFF + (wg * 64 + ww * 16 + g + 8) * 4);
#pragma unroll
        for (int t = 0; t < 28; t += 2) {
          const float* a = t < 16 ? &accA[4 * t] : &accB[4 * (t - 16)];
          stsm4(hrow + (t >> 3) * 8192 + ((((t & 7) + (lane >> 4)) ^ (lane & 7)) << 4),
                gelu2(a[0] * s0, a[1] * s0), gelu2(a[2] * s1, a[3] * s1), gelu2(a[4] * s0, a[5] * s0), gelu2(a[6] * s1, a[7] * s1));
        }
      }
      fence_async_smem();
      __syncwarp();
      if (lane == 0) mbar_arrive(BAR(B_HST + wg));
    }
    {
    FRESH_SB();
    mbar_wait(BAR(B_KRDY), 0);
    mbar_wait(BAR(B_XT), 0);
    {
      float acc[8][4];
      {
        float full[16][4];
        const uint32_t taps = sb + SSM_OFF + ww * TAP_CH, xt = sb + XT_OFF + ww * XT_CH;
        conv_near(full, taps, xt, wg * 4, lane);
        mbar_wait(BAR(B_HFREE), 0);
        const uint32_t slot = sb + ST_OFF + ww * 4096 + (wg ^ 1) * 2048 + lane * 16;
        if (wg == 0) {
#pragma unroll
          for (int j = 0; j < 8; j += 2)
            sts128(slot + j * 256, pack2(full[8 + j][0], full[8 + j][1]), pack2(full[8 + j][2], full[8 + j][3]), pack2(full[9 + j][0], full[9 + j][1]), pack2(full[9 + j][2], full[9 + j][3]));
#pragma unroll
          for (int j = 0; j < 32; j++) acc[j >> 2][j & 3] = full[j >> 2][j & 3];
        } else {
#pragma unroll
          for (int j = 0; j < 8; j += 2)
            sts128(slot + j * 256, pack2(full[j][0], full[j][1]), pack2(full[j][2], full[j][3]), pack2(full[1 + j][0], full[1 + j][1]), pack2(full[1 + j][2], full[1 + j][3]));
#pragma unroll
          for (int j = 0; j < 32; j++) acc[j >> 2][j & 3] = full[8 + (j >> 2)][j & 3];
        }
      }
      bar_sync(5 + ww, 96);
      const uint32_t zo = wg * 2048 + (lane >> 4) * 256 + (lane & 7) * 32 + (lane & 8) * 2;
#pragma unroll
      for (int j = 0; j < 8; j += 2) {
        uint32_t r[4];
        ldsm4t(r[0], r[1], r[2], r[3], sb + U_OFF + ww * U_CH + zo + j * 256);
        const uint4 o = lds<uint4>(sb + ST_OFF + ww * 4096 + wg * 2048 + lane * 16 + j * 256);
#pragma unroll
        for (int k = 0; k < 4; k++) {
          acc[j + (k >> 1)][2 * (k & 1)] += bf_lo(r[k]) + bf_lo((&o.x)[k]);
          acc[j + (k >> 1)][2 * (k & 1) + 1] += bf_hi(r[k]) + bf_hi((&o.x)[k]);
        }
      }
      __syncwarp();
      const uint32_t za = sb + ST_OFF + ww * 4096 + zo;
#pragma unroll
      for (int j = 0; j < 8; j += 2)
        asm volatile("stmatrix.sync.aligned.m8n8.x4.trans.shared.b16 [%0], {%1,%2,%3,%4};" ::"r"(za + j * 256), "r"(pack2(acc[j][0], acc[j][1])),
                     "r"(pack2(acc[j][2], acc[j][3])), "r"(pack2(acc[j + 1][0], acc[j + 1][1])), "r"(pack2(acc[j + 1][2], acc[j + 1][3])) : "memory");
      fence_async_smem();
    }
    __syncwarp();
    if (lane == 0) mbar_arrive(BAR(B_CONV));
    float acc[64];
#pragma unroll 1
    for (int it = 0; it < 14; it++) {
      const int s = it & 3;
      mbar_wait(BAR(B_FULL2 + s), (it >> 2) & 1);
      const uint32_t base = sb + RING_BYTES - S2_BYTES * (s + 1);
      const uint64_t da = mk_desc(base + wg * 8192, 16, 1024, 1), db = mk_desc(base + 16384, 8192, 1024, 1);
      WG_FENCE();
#pragma unroll
      for (int kk = 0; kk < 4; kk++) wgmma_n128_tb(acc, da + 2 * kk, db + 128 * kk, (it | kk) != 0);
      WG_COMMIT();
      WG_WAIT(1);
      if (it > 0 && lane == 0) mbar_arrive(BAR(B_EMPTY2 + ((it - 1) & 3)));
    }
    WG_WAIT(0);
    pin(acc);
    mbar_wait_cluster(BAR(B_PFREE), 0);
#pragma unroll
    for (int q = 0; q < 4; q++)
      asm volatile("st.async.weak.shared::cluster.mbarrier::complete_tx::bytes.v4.b32 [%0], {%1,%2,%3,%4}, [%5];"
                   ::"r"(rsb + RED_OFF + tid * 16 + q * 4096), "r"(pack2(acc[32 + 8 * q], acc[33 + 8 * q])), "r"(pack2(acc[34 + 8 * q], acc[35 + 8 * q])),
                     "r"(pack2(acc[36 + 8 * q], acc[37 + 8 * q])), "r"(pack2(acc[38 + 8 * q], acc[39 + 8 * q])), "r"(rsb + BAR_OFF + 8 * B_RED) : "memory");
    mbar_wait(BAR(B_BASE), 0);
#pragma unroll
    for (int q = 0; q < 4; q++) {
      const uint4 p = lds<uint4>(sb + BASE_OFF + q * 4096 + tid * 16);
#pragma unroll
      for (int k = 0; k < 4; k++) {
        acc[8 * q + 2 * k] = fmaf(acc[8 * q + 2 * k], 1.f / GK, bf_lo((&p.x)[k]));
        acc[8 * q + 2 * k + 1] = fmaf(acc[8 * q + 2 * k + 1], 1.f / GK, bf_hi((&p.x)[k]));
      }
    }
    mbar_wait_cluster(BAR(B_RED), 0);
#pragma unroll
    for (int q = 0; q < 4; q++) {
      const uint4 p = lds<uint4>(sb + RED_OFF + q * 4096 + tid * 16);
      uint32_t o[4];
#pragma unroll
      for (int k = 0; k < 4; k++) o[k] = pack2(fmaf(bf_lo((&p.x)[k]), 1.f / GK, acc[8 * q + 2 * k]), fmaf(bf_hi((&p.x)[k]), 1.f / GK, acc[8 * q + 2 * k + 1]));
      stsm4(sb + ST_OFF + (wg * 64 + ww * 16 + (lane & 15)) * 128 + (((2 * q + (lane >> 4)) ^ (lane & 7)) << 4), o[0], o[1], o[2], o[3]);
    }
    __syncwarp();
#pragma unroll
      for (int i = 0; i < 4; i++) {
        const int r = i * 4 + (lane >> 3);
        *reinterpret_cast<uint4*>(P.out + (rb * 128 + warp * 16 + r) * D_ + oc + (lane & 7) * 8) =
            lds<uint4>(sb + ST_OFF + (warp * 16 + r) * 128 + (((lane ^ r) & 7) << 4));
      }
    }
  }
}

typedef CUresult (*EncodeFn)(CUtensorMap*, CUtensorMapDataType, cuuint32_t, void*, const cuuint64_t*, const cuuint64_t*,
                             const cuuint32_t*, const cuuint32_t*, CUtensorMapInterleave, CUtensorMapSwizzle,
                             CUtensorMapL2promotion, CUtensorMapFloatOOBfill);

CUtensorMap make_map(EncodeFn enc, const void* ptr, int rank, const cuuint64_t* dims, const cuuint64_t* strides,
                     const cuuint32_t* box, CUtensorMapSwizzle swz) {
  CUtensorMap m;
  const cuuint32_t es[3] = {1, 1, 1};
  enc(&m, CU_TENSOR_MAP_DATA_TYPE_BFLOAT16, rank, const_cast<void*>(ptr), dims, strides, box, es, CU_TENSOR_MAP_INTERLEAVE_NONE,
      swz, CU_TENSOR_MAP_L2_PROMOTION_L2_128B, CU_TENSOR_MAP_FLOAT_OOB_FILL_NONE);
  return m;
}

}

extern "C" void kernel_launch(void* const* d_in, const int* in_sizes, int n_in, void* d_out, int out_size) {
  (void)in_sizes; (void)n_in; (void)out_size;
  typedef const __nv_bfloat16* bp;
  Params P = {(bp)d_in[0], (bp)d_in[1], (bp)d_in[2], (bp)d_in[3], (bp)d_in[4], (bp)d_in[5], (bp)d_in[6], (bp)d_in[7],
              (bp)d_in[8], (bp)d_in[10], (bp)d_in[11], (bp)d_in[12], (bp)d_in[13], (__nv_bfloat16*)d_out};
  void* fn = nullptr;
  cudaDriverEntryPointQueryResult qr;
  cudaGetDriverEntryPoint("cuTensorMapEncodeTiled", &fn, cudaEnableDefault, &qr);
  EncodeFn enc = (EncodeFn)fn;
  void *ph, *pz;
  cudaGetSymbolAddress(&ph, g_h);
  cudaGetSymbolAddress(&pz, g_zT);
  const cuuint64_t dX[2] = {D_, L_}, sX[1] = {D_ * 2};
  const cuuint32_t bX1[2] = {32, 128}, bXe[2] = {64, 128}, bW1[3] = {64, 32, 1}, b64[3] = {64, 64, 1}, bZ[3] = {64, 64, 2};
  const cuuint64_t dW1[3] = {64, D_, F_ / 64}, dW1h[3] = {32, D_, F_ / 32}, sF[2] = {F_ * 2, 128}, sFh[2] = {F_ * 2, 64};
  const cuuint64_t dHs[3] = {64, L_, F_ / 64}, dHh[3] = {32, L_, F_ / 32}, dHl[2] = {F_, L_};
  const cuuint64_t dW2[3] = {64, F_, D_ / 64}, sW2[2] = {D_ * 2, 128}, dZ[3] = {64, D_, L_ / 64}, sZ[2] = {L_ * 2, 128};
  CUtensorMap tmX1 = make_map(enc, P.x, 2, dX, sX, bX1, CU_TENSOR_MAP_SWIZZLE_64B);
  CUtensorMap tmW1s = make_map(enc, P.w1, 3, dW1, sF, bW1, CU_TENSOR_MAP_SWIZZLE_128B);
  CUtensorMap tmW1h = make_map(enc, P.w1, 3, dW1h, sFh, bW1, CU_TENSOR_MAP_SWIZZLE_128B);
  CUtensorMap tmHs = make_map(enc, ph, 3, dHs, sF, b64, CU_TENSOR_MAP_SWIZZLE_128B);
  CUtensorMap tmHh = make_map(enc, ph, 3, dHh, sFh, b64, CU_TENSOR_MAP_SWIZZLE_128B);
  CUtensorMap tmHld = make_map(enc, ph, 2, dHl, sF, bXe, CU_TENSOR_MAP_SWIZZLE_128B);
  CUtensorMap tmW2 = make_map(enc, P.w2, 3, dW2, sW2, b64, CU_TENSOR_MAP_SWIZZLE_128B);
  CUtensorMap tmXe = make_map(enc, P.x, 2, dX, sX, bXe, CU_TENSOR_MAP_SWIZZLE_128B);
  CUtensorMap tmZ = make_map(enc, pz, 3, dZ, sZ, bZ, CU_TENSOR_MAP_SWIZZLE_128B);
  const cuuint64_t dXT[3] = {16, D_, L_ / 16}, sXT[2] = {32, D_ * 32};
  const cuuint32_t bXT[3] = {16, 1, 128};
  void* pxt;
  cudaGetSymbolAddress(&pxt, g_xnT);
  CUtensorMap tmXT = make_map(enc, pxt, 3, dXT, sXT, bXT, CU_TENSOR_MAP_SWIZZLE_NONE);
  cudaFuncSetAttribute(fused_kernel, cudaFuncAttributeMaxDynamicSharedMemorySize, SMEM_BYTES);
  fused_kernel<<<NCTA, 512, SMEM_BYTES, cudaStreamPerThread>>>(P, tmX1, tmW1s, tmW1h, tmHs, tmHh, tmHld, tmW2, tmXe, tmZ, tmXT);
}
```
